```python
import torch

def _softmax(x, axis=-1):
    return torch.softmax(x, dim=axis)
def _gelu(x):
    return torch.nn.functional.gelu(x, approximate="tanh")
def _silu(x):
    return torch.nn.functional.silu(x)
def _sigmoid(x):
    return torch.sigmoid(x)
def _layernorm(x, axis=-1, eps=1e-5):
    m = x.mean(dim=axis, keepdim=True)
    v = x.var(dim=axis, keepdim=True, unbiased=False)
    return (x - m) / torch.sqrt(v + eps)
def _scatter_add(tgt, idx, src, axis=0):
    return tgt.clone().index_add_(axis, idx, src)
def _segment_sum(src, seg, n):
    out = torch.zeros((n,) + src.shape[1:], dtype=src.dtype)
    return out.index_add_(0, seg, src)
def _pad(x, pw):
    flat = tuple(v for pair in reversed(pw) for v in pair)
    return torch.nn.functional.pad(x, flat)

kernel_name = 'parallel_sum__sliding_block_cached__glu_gated_bilinear__decode'

def setup_inputs():

    _w = (lambda a: (lambda t: t.to(torch.bfloat16) if t.is_floating_point() else t)(torch.as_tensor(a)))
    def _A_setup():
        B, Sq, D = 2, 1, 448
        Hq, Hkv, Sk, Dh = 16, 8, 32768, 256
        assert Hq % Hkv == 0, (Hq, Hkv)
        return {
            "x": _w((lambda *s: torch.randn(*s, dtype=torch.bfloat16) * 0.05)(B, Sq, D)),
            "k_cache": _w((lambda *s: torch.randn(*s, dtype=torch.bfloat16) * 1.6)(B, Hkv, Sk, Dh)),
            "v_cache": _w((lambda *s: torch.randn(*s, dtype=torch.bfloat16) * 0.8)(B, Hkv, Sk, Dh)),
            "wq": _w((lambda *s: torch.randn(*s, dtype=torch.bfloat16) * 1.6)(D, Hq * Dh) * (D ** -0.5)),
            "wo": _w((lambda *s: torch.randn(*s, dtype=torch.bfloat16) * 0.8)(Hq * Dh, D) * ((Hq * Dh) ** -0.5)),
        }
    _A_in = _A_setup()

    def _B_setup():
        B, S, D, F = 2, 1, 448, 1792
        return {
            "x": _w((lambda *s: torch.randn(*s, dtype=torch.bfloat16) * 0.05)(B, S, D)),
            "w_gate": _w((lambda *s: torch.randn(*s, dtype=torch.bfloat16) * 0.4)(D, F) * (D ** -0.5)),
            "w_up": _w((lambda *s: torch.randn(*s, dtype=torch.bfloat16) * 0.4)(D, F) * (D ** -0.5)),
            "w_down": _w((lambda *s: torch.randn(*s, dtype=torch.bfloat16) * 0.4)(F, D) * (F ** -0.5)),
        }
    _B_in = _B_setup()

    return {
        "A_x": _A_in["x"],
        "A_k_cache": _A_in["k_cache"],
        "A_v_cache": _A_in["v_cache"],
        "A_wq": _A_in["wq"],
        "A_wo": _A_in["wo"],
        "B_x": _B_in["x"],
        "B_w_gate": _B_in["w_gate"],
        "B_w_up": _B_in["w_up"],
        "B_w_down": _B_in["w_down"],
    }

def reference(A_x, A_k_cache, A_v_cache, A_wq, A_wo, B_x, B_w_gate, B_w_up, B_w_down):
    def _A_ref(x, k_cache, v_cache, wq, wo):
        B, Sq, D = x.shape
        Hq, Dh = 16, 256
        Hkv, Sk = k_cache.shape[1], k_cache.shape[2]
        W = min(4096, max(256, Sk // 4))
        rep = Hq // Hkv
        q = (lambda x, *d: x.permute(*d))((x @ wq).reshape(B, Sq, Hq, Dh), 0, 2, 1, 3)
        k = (lambda x, n, axis: torch.repeat_interleave(x, n, dim=axis))(k_cache[:, :, Sk - W:, :], rep, axis=1)
        v = (lambda x, n, axis: torch.repeat_interleave(x, n, dim=axis))(v_cache[:, :, Sk - W:, :], rep, axis=1)
        scores = torch.einsum("bhqd,bhkd->bhqk", q, k) * (Dh ** -0.5)
        p = _softmax(scores, axis=-1)
        o = torch.einsum("bhqk,bhkd->bhqd", p, v)
        return (lambda x, *d: x.permute(*d))(o, 0, 2, 1, 3).reshape(B, Sq, Hq * Dh) @ wo

    def _B_ref(x, w_gate, w_up, w_down):
        g = torch.einsum("bsd,df->bsf", x, w_gate)
        u = torch.einsum("bsd,df->bsf", x, w_up)
        h = g * u
        return torch.einsum("bsf,fd->bsd", h, w_down)

    x = A_x
    xn = _layernorm(x, axis=-1)
    return x + _A_ref(xn, A_k_cache, A_v_cache, A_wq, A_wo) + _B_ref(xn, B_w_gate, B_w_up, B_w_down)
```

```cpp
#include <cuda_runtime.h>
#include <cuda.h>
#include <cuda_bf16.h>
#include <stdint.h>

namespace {

constexpr int D_MODEL = 448;
constexpr int SK = 32768;
constexpr int WIN = 4096;
constexpr int NCTA = 128;
constexpr int NFFN = 112;
constexpr int STAGE = 16384;
#define NS_STAGES 13
constexpr int NS = NS_STAGES;
#define DEPTH0 4
#define DEPTH1 8
#define DEPTH2 8
#define PACE 645
#define LEAD 1.0f
constexpr int ST_WQ = 0;
constexpr int ST_K = 2;
constexpr int ST_V = 18;
constexpr int ST_G = 34;
constexpr int ST_WO = 36;
constexpr int ST_WD = 38;
constexpr int NST = 39;
constexpr int NEMPTY = NST - NS;
constexpr int BAR_STAT = NST + NEMPTY;
constexpr int BAR_H = BAR_STAT + 1;
constexpr int BAR_O = BAR_STAT + 2;
constexpr int NBAR = BAR_STAT + 3;
constexpr int NTHREADS = 384;
#define SLOW_NS 4000
#define QPOLL_ST 5
#define OPOLL_ST 27
#define ILV
#define FAST_ST (ST_V + 12)
constexpr int N0 = DEPTH0;
constexpr int SMEM_BYTES = NS * STAGE + 1024;
constexpr unsigned SPIN_LIMIT = 1u << 24;

#define TRACE(i) do {} while (0)

__device__ unsigned int g_epoch[NCTA];
__device__ __align__(128) unsigned int g_qbuf[2][4096];
__device__ __align__(128) float g_oval[8][16][16][32];
__device__ __align__(128) float g_oml[16][32];
__device__ __align__(128) float g_fbuf[NFFN][NCTA][8];

__device__ __forceinline__ unsigned long long globaltimer() {
    unsigned long long t;
    asm volatile("mov.u64 %0, %globaltimer;" : "=l"(t));
    return t;
}
__device__ __forceinline__ uint32_t globaltimer_lo() {
    uint32_t t;
    asm volatile("mov.u32 %0, %globaltimer_lo;" : "=r"(t));
    return t;
}
__device__ __forceinline__ uint32_t smem_u32(const void* p) {
    return (uint32_t)__cvta_generic_to_shared(p);
}
__device__ __forceinline__ void mbar_init(uint32_t bar, uint32_t cnt) {
    asm volatile("mbarrier.init.shared::cta.b64 [%0], %1;" ::"r"(bar), "r"(cnt) : "memory");
}
__device__ __forceinline__ void mbar_expect_tx(uint32_t bar, uint32_t bytes) {
    asm volatile("mbarrier.arrive.expect_tx.shared::cta.b64 _, [%0], %1;" ::"r"(bar), "r"(bytes) : "memory");
}
__device__ __forceinline__ void mbar_arrive(uint32_t bar) {
    asm volatile("mbarrier.arrive.shared::cta.b64 _, [%0];" ::"r"(bar) : "memory");
}
__device__ __forceinline__ void mbar_wait(uint32_t bar) {
    unsigned n = 0;
    uint32_t ok;
    do {
        asm volatile(
            "{\n.reg .pred p;\n"
            "mbarrier.try_wait.parity.shared::cta.b64 p, [%1], 0;\n"
            "selp.u32 %0, 1, 0, p;\n}"
            : "=r"(ok) : "r"(bar) : "memory");
        if (++n > SPIN_LIMIT) __trap();
    } while (!ok);
}
__device__ __forceinline__ void mbar_nap(uint32_t bar, uint32_t ns) {
    asm volatile(
        "{\n.reg .pred p;\n"
        "mbarrier.try_wait.parity.shared::cta.b64 p, [%0], 0, %1;\n}"
        ::"r"(bar), "r"(ns) : "memory");
}
__device__ __forceinline__ uint32_t mbar_test(uint32_t bar) {
    uint32_t ok;
    asm volatile(
        "{\n.reg .pred p;\n"
        "mbarrier.test_wait.parity.shared::cta.b64 p, [%1], 0;\n"
        "selp.u32 %0, 1, 0, p;\n}"
        : "=r"(ok) : "r"(bar) : "memory");
    return ok;
}
__device__ __forceinline__ void tma_3d(uint32_t dst, const void* m, int c0, int c1, int c2, uint32_t bar) {
    asm volatile(
        "cp.async.bulk.tensor.3d.shared::cluster.global.mbarrier::complete_tx::bytes [%0], [%1, {%3, %4, %5}], [%2];"
        ::"r"(dst), "l"(m), "r"(bar), "r"(c0), "r"(c1), "r"(c2) : "memory");
}
__device__ __forceinline__ void prefetch_map(const CUtensorMap* m) {
    asm volatile("prefetch.tensormap [%0];" ::"l"(m) : "memory");
}
__device__ __forceinline__ void prefetch_l2(const void* p, uint32_t bytes) {
    asm volatile("cp.async.bulk.prefetch.L2.global [%0], %1;" ::"l"(p), "r"(bytes) : "memory");
}
__device__ __forceinline__ void ldsm4(uint32_t (&a)[4], uint32_t addr) {
    asm volatile("ldmatrix.sync.aligned.m8n8.x4.shared.b16 {%0,%1,%2,%3}, [%4];"
                 : "=r"(a[0]), "=r"(a[1]), "=r"(a[2]), "=r"(a[3]) : "r"(addr) : "memory");
}
__device__ __forceinline__ void ldsm4t(uint32_t (&a)[4], uint32_t addr) {
    asm volatile("ldmatrix.sync.aligned.m8n8.x4.trans.shared.b16 {%0,%1,%2,%3}, [%4];"
                 : "=r"(a[0]), "=r"(a[1]), "=r"(a[2]), "=r"(a[3]) : "r"(addr) : "memory");
}
__device__ __forceinline__ void mma16816(float (&c)[4], const uint32_t (&a)[4], uint32_t b0, uint32_t b1) {
    asm volatile(
        "mma.sync.aligned.m16n8k16.row.col.f32.bf16.bf16.f32 {%0,%1,%2,%3}, {%4,%5,%6,%7}, {%8,%9}, {%0,%1,%2,%3};"
        : "+f"(c[0]), "+f"(c[1]), "+f"(c[2]), "+f"(c[3])
        : "r"(a[0]), "r"(a[1]), "r"(a[2]), "r"(a[3]), "r"(b0), "r"(b1));
}
__device__ __forceinline__ void bar_sync(int id, int n) {
    asm volatile("bar.sync %0, %1;" ::"r"(id), "r"(n) : "memory");
}
__device__ __forceinline__ void bar_arrive(int id, int n) {
    asm volatile("bar.arrive %0, %1;" ::"r"(id), "r"(n) : "memory");
}
__device__ __forceinline__ float bf16r(float x) { return __bfloat162float(__float2bfloat16_rn(x)); }
__device__ __forceinline__ uint32_t pack_bf16(float lo, float hi) {
    __nv_bfloat162 v = __floats2bfloat162_rn(lo, hi);
    return *reinterpret_cast<uint32_t*>(&v);
}
__device__ __forceinline__ float ex2(float x) {
    float y;
    asm("ex2.approx.ftz.f32 %0, %1;" : "=f"(y) : "f"(x));
    return y;
}
__device__ __forceinline__ void st_relaxed(void* p, uint32_t v) {
    asm volatile("st.relaxed.gpu.global.u32 [%0], %1;" ::"l"(p), "r"(v) : "memory");
}
__device__ __forceinline__ uint32_t ld_relaxed(const void* p) {
    uint32_t v;
    asm volatile("ld.relaxed.gpu.global.u32 %0, [%1];" : "=r"(v) : "l"(p) : "memory");
    return v;
}
__device__ __forceinline__ uint2 ld_relaxed2(const void* p) {
    uint2 v;
    asm volatile("ld.relaxed.gpu.global.v2.u32 {%0,%1}, [%2];" : "=r"(v.x), "=r"(v.y) : "l"(p) : "memory");
    return v;
}
__device__ __forceinline__ uint4 ld_relaxed4(const void* p) {
    uint4 v;
    asm volatile("ld.relaxed.gpu.global.v4.u32 {%0,%1,%2,%3}, [%4];"
                 : "=r"(v.x), "=r"(v.y), "=r"(v.z), "=r"(v.w) : "l"(p) : "memory");
    return v;
}
__device__ __forceinline__ void ld_relaxed2_if(uint2& v, const void* p, uint32_t pred) {
    asm volatile("{\n.reg .pred p;\nsetp.ne.u32 p, %3, 0;\n@p ld.relaxed.gpu.global.v2.u32 {%0,%1}, [%2];\n}"
                 : "+r"(v.x), "+r"(v.y) : "l"(p), "r"(pred) : "memory");
}
__device__ __forceinline__ void ld_relaxed4_if(uint4& v, const void* p, uint32_t pred) {
    asm volatile("{\n.reg .pred p;\nsetp.ne.u32 p, %5, 0;\n@p ld.relaxed.gpu.global.v4.u32 {%0,%1,%2,%3}, [%4];\n}"
                 : "+r"(v.x), "+r"(v.y), "+r"(v.z), "+r"(v.w) : "l"(p), "r"(pred) : "memory");
}
__device__ __forceinline__ uint32_t tagf(float v, uint32_t tag4) { return (__float_as_uint(v) & ~15u) | tag4; }
__device__ __forceinline__ float sel4(const float (&c)[4], int t) {
    float lo = (t & 1) ? c[1] : c[0];
    float hi = (t & 1) ? c[3] : c[2];
    return (t & 2) ? hi : lo;
}

struct Maps {
    CUtensorMap m[7];
};

__global__ void __launch_bounds__(NTHREADS, 1)
fused_decode_kernel(const __grid_constant__ Maps maps, const __nv_bfloat16* __restrict__ x,
                    __nv_bfloat16* __restrict__ out, const unsigned char* __restrict__ wq_raw,
                    const unsigned char* __restrict__ k_raw) {
    extern __shared__ unsigned char smem_raw[];
    __shared__ __align__(8) uint64_t bars[NBAR];
    __shared__ __align__(16) int4 sched_s[NST];
    __shared__ __align__(16) float2 s_s[512];
    __shared__ __align__(16) uint32_t p_s[512];
    __shared__ __align__(16) uint32_t xn_s[2 * 228];
    __shared__ __align__(16) uint32_t q_s[2 * 132];
    __shared__ __align__(16) uint32_t oh_s[2][28];
    __shared__ __align__(16) float2 wmax_s[8];
    __shared__ __align__(16) float2 wsum_s[8];
    __shared__ __align__(8) float fac_s[2];

    const int tid = threadIdx.x;
    const int warp = tid >> 5;
    const int lane = tid & 31;
    const int cta = blockIdx.x;
    const int bh = cta >> 3;
    const int sp = cta & 7;
    const int b = bh >> 3;
    const int hkv = bh & 7;
    const bool has_ffn = cta < NFFN;
    const uint32_t ring = (smem_u32(smem_raw) + 1023u) & ~1023u;
    const uint32_t fullb = smem_u32(bars);
    const uint32_t emptyb = fullb + NST * 8;
    const int kvrow = bh * SK + (SK - WIN) + sp * 32;
#define TROW(j) (kvrow + (j) * 256)

    uint32_t xr[7];
    uint32_t t0 = 0;
    if (warp == 8) {
        if (lane == 0) {
#pragma unroll
            for (int i = 0; i < N0; i++) mbar_init(fullb + i * 8, 1);
            asm volatile("fence.proxy.async.shared::cta;" ::: "memory");
#pragma unroll
            for (int i = 0; i < N0; i++) {
                mbar_expect_tx(fullb + i * 8, i < ST_K ? 14336 : STAGE);
                if (i < ST_K) tma_3d(ring + i * STAGE, &maps.m[0], cta * 32, 0, i, fullb + i * 8);
                else tma_3d(ring + i * STAGE, &maps.m[1], 0, TROW(i - ST_K), 0, fullb + i * 8);
            }
            t0 = globaltimer_lo();
            TRACE(10);
#pragma unroll
            for (int i = 2; i < 7; i++) prefetch_map(&maps.m[i]);
        }
    } else if (warp < 2) {
        if (tid == 0) TRACE(0);
        const uint32_t* xp = reinterpret_cast<const uint32_t*>(x) + warp * 224;
#pragma unroll
        for (int i = 0; i < 7; i++) xr[i] = __ldg(xp + lane + 32 * i);
    } else if (warp == 9) {
        for (int i = lane; i < NST; i += 32) {
            int map, bytes = STAGE, c0 = 0, c1, c2 = 0;
            if (i < ST_K + 16) {
                map = 1; c1 = TROW(i - ST_K);
            } else if (i >= ST_V && i < ST_V + 16) {
                map = 2; c1 = TROW(i - ST_V);
            } else if (i < ST_WO) {
                map = 3 + i - ST_G; c0 = cta * 16; c1 = 0; bytes = has_ffn ? 14336 : 0;
            } else if (i < ST_WD) {
                map = 5; c1 = hkv * 512 + (b * 8 + sp) * 32; c2 = (i - ST_WO) * 4;
            } else {
                map = 6; c1 = cta * 16; bytes = has_ffn ? 14336 : 0;
            }
            const int dep = i - (i < ST_V + 16 ? DEPTH1 : DEPTH2);
            const float u = (float)i - 0.25f - 0.235f * (float)(i > ST_G + 1 ? 2 : i > ST_G ? 1 : 0) -
                            (i == ST_WD ? 0.25f : 0.f) - LEAD;
            const int tm = u > 0.f ? (int)(u * (float)PACE) : 0;
            sched_s[i] = make_int4((map * 128) | (bytes << 16), c0, c1, c2 | ((dep < 0 ? 0 : dep) << 8) | (tm << 16));
        }
    } else if (lane == 0 && warp < 8) {
#pragma unroll 1
        for (int i = N0 + warp - 2; i < NBAR; i += 6) {
            const int e = i - NST;
            mbar_init(fullb + i * 8, (e >= ST_V && e < NEMPTY) ? 8 : (e >= 0 && e < ST_K) ? 2 : 1);
        }
        asm volatile("fence.proxy.async.shared::cta;" ::: "memory");
    }
    const uint32_t epoch = ld_relaxed(&g_epoch[cta]);
    __syncthreads();

    if (warp == 8) {
        if (lane == 0) {
            int slot = N0;
#pragma unroll 1
            for (int i = N0; i < NST; i++) {
                const int4 e = sched_s[i];
                if (i >= DEPTH1) mbar_wait(fullb + ((e.w >> 8) & 0xff) * 8);
                if (i >= NS) mbar_wait(emptyb + (i - NS) * 8);
                if (PACE > 0) {
                    const uint32_t tm = (uint32_t)e.w >> 16;
                    unsigned n = 0;
                    while (globaltimer_lo() - t0 < tm && ++n < 4096u) {}
                }
                const uint32_t bytes = (uint32_t)e.x >> 16;
                mbar_expect_tx(fullb + i * 8, bytes);
                if (bytes)
                    tma_3d(ring + slot * STAGE, reinterpret_cast<const unsigned char*>(&maps) + (e.x & 0xffff), e.y,
                           e.z, e.w & 0xff, fullb + i * 8);
                if (++slot == NS) slot = 0;
            }
            g_epoch[cta] = epoch + 1;
            TRACE(1);
        }
        return;
    }

    const uint32_t tag16 = (epoch % 65535u) + 1u;
    const uint32_t tag4 = (epoch % 15u) + 1u;
    const int g = lane >> 2;
    const int t = lane & 3;
    const int lrow = (lane & 7) + ((lane >> 4) << 3);
    const int lcol = (lane >> 3) & 1;
    const float SC = 0.0625f * 1.4426950408889634f;

    if (warp == 9) {
        bar_sync(4, 96);
        if (has_ffn) {
            uint32_t xf[28][2];
#pragma unroll
            for (int ks = 0; ks < 28; ks++) {
                xf[ks][0] = xn_s[ks * 8 + (g & 1) * 228 + t];
                xf[ks][1] = xn_s[ks * 8 + (g & 1) * 228 + t + 4];
            }
            float hv = 1.f;
#pragma unroll 1
            for (int j = 0; j < 2; j++) {
                const uint32_t base = ring + ((ST_G + j) % NS) * STAGE + lrow * 32 + ((lcol ^ ((lrow >> 2) & 1)) << 4);
                float acc[4][4] = {};
                mbar_wait(fullb + (ST_G + j) * 8);
#pragma unroll
                for (int ks = 0; ks < 28; ks++) {
                    uint32_t a[4];
                    ldsm4t(a, base + ks * 512);
                    mma16816(acc[ks & 3], a, xf[ks][0], xf[ks][1]);
                }
                float c[4];
#pragma unroll
                for (int i = 0; i < 4; i++) c[i] = (acc[0][i] + acc[1][i]) + (acc[2][i] + acc[3][i]);
                hv *= bf16r(sel4(c, t));
                if (ST_G < NEMPTY) {
                    __syncwarp();
                    if (lane == 0) mbar_arrive(emptyb + (ST_G + j) * 8);
                }
            }
            reinterpret_cast<__nv_bfloat16*>(&oh_s[t & 1][16])[g + (t >> 1) * 8] = __float2bfloat16_rn(hv);
            __syncwarp();
            if (lane == 0) mbar_arrive(fullb + BAR_H * 8);
        } else if (ST_G < NEMPTY && lane < 2) {
            mbar_arrive(emptyb + (ST_G + lane) * 8);
        }
        if (lane == 0) TRACE(15);
        return;
    }

    if (warp == 10) {
        const float* ib = &g_oval[hkv][b * 8 + sp][(lane >> 4) * 8][(lane & 15) * 2];
        mbar_wait(fullb + (OPOLL_ST) * 8);
        uint2 v[8] = {};
        unsigned n = 0;
        uint32_t pend = 0xffu;
        while (true) {
#pragma unroll
            for (int s = 0; s < 8; s++) ld_relaxed2_if(v[s], ib + s * 32, pend & (1u << s));
            pend = 0;
#pragma unroll
            for (int s = 0; s < 8; s++)
                if (((v[s].x ^ tag4) | (v[s].y ^ tag4)) & 15u) pend |= 1u << s;
            if (!__any_sync(0xffffffffu, pend)) break;
            if (++n > SPIN_LIMIT) __trap();
            mbar_nap(fullb + FAST_ST * 8, SLOW_NS);
        }
        float o0 = 0.f, o1 = 0.f;
#pragma unroll
        for (int s = 0; s < 8; s++) {
            o0 += __uint_as_float(v[s].x);
            o1 += __uint_as_float(v[s].y);
        }
        oh_s[lane >> 4][lane & 15] = pack_bf16(o0, o1);
        __syncwarp();
        if (lane == 0) mbar_arrive(fullb + BAR_O * 8);
        if (lane == 0) TRACE(7);
        return;
    }
    if (warp == 11) {
        {
            uint32_t w;
            unsigned n = 0;
            while (true) {
                w = ld_relaxed(&g_oml[bh][lane]);
                if (__all_sync(0xffffffffu, (w & 15u) == tag4)) break;
                if (++n > SPIN_LIMIT) __trap();
                __nanosleep(500);
            }
            const float val = __uint_as_float(w & ~15u);
            const float ms = __shfl_sync(0xffffffffu, val, lane & ~1);
            float mm = ms;
#pragma unroll
            for (int o = 4; o < 32; o <<= 1) mm = fmaxf(mm, __shfl_xor_sync(0xffffffffu, mm, o));
            float den = val * ex2((ms - mm) * SC);
#pragma unroll
            for (int o = 4; o < 32; o <<= 1) den += __shfl_xor_sync(0xffffffffu, den, o);
            if ((lane >> 2) == sp && (lane & 1)) fac_s[(lane >> 1) & 1] = __fdividef(ex2((ms - mm) * SC), den);
            __syncwarp();
            if (lane == 0) mbar_arrive(fullb + BAR_STAT * 8);
            if (lane == 0) TRACE(11);
        }
        if (!has_ffn) return;
        const int oidx = (lane & 1) * D_MODEL + cta * 4 + ((lane >> 1) & 3);
        const float xres = __bfloat162float(x[oidx]);
        const float* fb = &g_fbuf[cta][lane >> 1][(lane & 1) * 4];
        mbar_wait(fullb + (OPOLL_ST) * 8);
        uint4 w[8] = {};
        unsigned n = 0;
        uint32_t pend = 0xffu;
        while (true) {
#pragma unroll
            for (int r = 0; r < 8; r++) ld_relaxed4_if(w[r], fb + r * 128, pend & (1u << r));
            pend = 0;
#pragma unroll
            for (int r = 0; r < 8; r++)
                if (((w[r].x ^ tag4) | (w[r].y ^ tag4) | (w[r].z ^ tag4) | (w[r].w ^ tag4)) & 15u) pend |= 1u << r;
            if (!__any_sync(0xffffffffu, pend)) break;
            if (++n > SPIN_LIMIT) __trap();
            mbar_nap(fullb + BAR_O * 8, SLOW_NS);
        }
        float a[4] = {};
#pragma unroll
        for (int r = 0; r < 8; r++) {
            a[0] += __uint_as_float(w[r].x);
            a[1] += __uint_as_float(w[r].y);
            a[2] += __uint_as_float(w[r].z);
            a[3] += __uint_as_float(w[r].w);
        }
#pragma unroll
        for (int o = 2; o < 32; o <<= 1)
#pragma unroll
            for (int i = 0; i < 4; i++) a[i] += __shfl_xor_sync(0xffffffffu, a[i], o);
        const float mine = sel4(a, lane & 3);
        const float other = __shfl_sync(0xffffffffu, sel4(a, (lane ^ 1) & 3), lane ^ 1);
        const float tot = (((lane >> 2) & 1) == (lane & 1)) ? mine : other;
        if (lane < 8) out[oidx] = __float2bfloat16_rn(xres + tot);
        if (lane == 0) TRACE(9);
        return;
    }

    if (warp < 2) {
        float v[14];
        float s = 0.f;
#pragma unroll
        for (int i = 0; i < 7; i++) {
            v[2 * i] = __uint_as_float(xr[i] << 16);
            v[2 * i + 1] = __uint_as_float(xr[i] & 0xffff0000u);
            s += v[2 * i] + v[2 * i + 1];
        }
#pragma unroll
        for (int o = 16; o > 0; o >>= 1) s += __shfl_xor_sync(0xffffffffu, s, o);
        const float mean = s * (1.0f / D_MODEL);
        float ss = 0.f;
#pragma unroll
        for (int i = 0; i < 14; i++) ss += (v[i] - mean) * (v[i] - mean);
#pragma unroll
        for (int o = 16; o > 0; o >>= 1) ss += __shfl_xor_sync(0xffffffffu, ss, o);
        const float mb = bf16r(mean);
        const float var = bf16r(ss * (1.0f / D_MODEL));
        const float rsd = __frcp_rn(bf16r(__fsqrt_rn(bf16r(var + 1e-5f))));
#pragma unroll
        for (int i = 0; i < 7; i++)
            xn_s[warp * 228 + lane + 32 * i] =
                pack_bf16(bf16r(v[2 * i] - mb) * rsd, bf16r(v[2 * i + 1] - mb) * rsd);
        bar_arrive(4, 96);
        bar_sync(3, 64);
        if (tid == 0) TRACE(2);

        float acc[2][4] = {};
#pragma unroll 1
        for (int hf = 0; hf < 2; hf++) {
            mbar_wait(fullb + (ST_WQ + hf) * 8);
            const uint32_t base = ring + (ST_WQ + hf) * STAGE;
#pragma unroll
            for (int ks = 0; ks < 14; ks++) {
                const int row = ks * 16 + lrow;
                uint32_t a[4];
                ldsm4t(a, base + row * 64 + (((warp * 2 + lcol) ^ ((row >> 1) & 3)) << 4));
                const int kk = (hf * 14 + ks) * 8 + (g & 1) * 228 + t;
                mma16816(acc[ks & 1], a, xn_s[kk], xn_s[kk + 4]);
            }
            __syncwarp();
            if (lane == 0) mbar_arrive(emptyb + (ST_WQ + hf) * 8);
        }
        float c[4];
#pragma unroll
        for (int i = 0; i < 4; i++) c[i] = acc[0][i] + acc[1][i];
        const float qv = sel4(c, t);
        const int col = cta * 32 + warp * 16 + g + (t >> 1) * 8;
        const uint32_t w = (uint32_t)__bfloat16_as_ushort(__float2bfloat16_rn(qv)) | (tag16 << 16);
        st_relaxed(&g_qbuf[t & 1][col], w);
        if (tid == 0) TRACE(3);
    } else if (warp >= 4) {
        const int j = tid - 128;
        const unsigned int* qp = &g_qbuf[b][hkv * 512 + j * 4];
        mbar_wait(fullb + QPOLL_ST * 8);
        uint4 w;
        unsigned n = 0;
        while (true) {
            w = ld_relaxed4(qp);
            if ((((w.x >> 16) ^ tag16) | ((w.y >> 16) ^ tag16) | ((w.z >> 16) ^ tag16) | ((w.w >> 16) ^ tag16)) == 0) break;
            if (++n > SPIN_LIMIT) __trap();
        }
        *reinterpret_cast<uint2*>(&q_s[(j >> 6) * 132 + (j & 63) * 2]) =
            make_uint2((w.x & 0xffffu) | (w.y << 16), (w.z & 0xffffu) | (w.w << 16));
    }
    bar_sync(1, 256);

    {
        uint32_t qf[16][2];
#pragma unroll
        for (int ks = 0; ks < 16; ks++) {
            qf[ks][0] = q_s[(g & 1) * 132 + ks * 8 + t];
            qf[ks][1] = q_s[(g & 1) * 132 + ks * 8 + 4 + t];
        }
        if (tid == 0 && qf[0][0] != 0x12345678u) TRACE(4);
        float mx0 = -INFINITY, mx1 = -INFINITY;
        const uint32_t koff = ((lane & 7) + ((lane >> 3) & 1) * 8) * 128;
#pragma unroll 1
        for (int it = 0; it < 2; it++) {
            const int tile = warp + it * 8;
            const int st = ST_K + tile;
            mbar_wait(fullb + st * 8);
            const uint32_t base = ring + (st % NS) * STAGE + koff;
            float acc[2][2][4] = {};
#pragma unroll
            for (int ks = 0; ks < 16; ks++) {
                const uint32_t off = (ks >> 2) * 4096 + ((((ks & 3) * 2 + (lane >> 4)) ^ (lane & 7)) << 4);
#pragma unroll
                for (int mt = 0; mt < 2; mt++) {
                    uint32_t a[4];
                    ldsm4(a, base + off + mt * 2048);
                    mma16816(acc[mt][ks & 1], a, qf[ks][0], qf[ks][1]);
                }
            }
            __syncwarp();
            if (lane == 0) mbar_arrive(emptyb + st * 8);
            const int mt = t >> 1;
            float e0, e1;
            {
                float a0 = acc[0][0][0] + acc[0][1][0], a1 = acc[0][0][1] + acc[0][1][1];
                float a2 = acc[0][0][2] + acc[0][1][2], a3 = acc[0][0][3] + acc[0][1][3];
                float b0 = acc[1][0][0] + acc[1][1][0], b1 = acc[1][0][1] + acc[1][1][1];
                float b2 = acc[1][0][2] + acc[1][1][2], b3 = acc[1][0][3] + acc[1][1][3];
                float l0 = (t & 1) ? a2 : a0, l1 = (t & 1) ? a3 : a1;
                float h0 = (t & 1) ? b2 : b0, h1 = (t & 1) ? b3 : b1;
                e0 = mt ? h0 : l0;
                e1 = mt ? h1 : l1;
            }
            e0 = bf16r(e0);
            e1 = bf16r(e1);
            mx0 = fmaxf(mx0, e0);
            mx1 = fmaxf(mx1, e1);
            s_s[tile * 32 + mt * 16 + (t & 1) * 8 + g] = make_float2(e0, e1);
        }
#pragma unroll
        for (int o = 16; o > 0; o >>= 1) {
            mx0 = fmaxf(mx0, __shfl_xor_sync(0xffffffffu, mx0, o));
            mx1 = fmaxf(mx1, __shfl_xor_sync(0xffffffffu, mx1, o));
        }
        if (lane == 0) wmax_s[warp] = make_float2(mx0, mx1);
    }
    bar_sync(1, 256);

    {
        float m0 = wmax_s[0].x, m1 = wmax_s[0].y;
#pragma unroll
        for (int i = 1; i < 8; i++) {
            m0 = fmaxf(m0, wmax_s[i].x);
            m1 = fmaxf(m1, wmax_s[i].y);
        }
        if (tid == 0 && m0 != 12345.678f) TRACE(5);
        const float4 sv = *reinterpret_cast<const float4*>(&s_s[tid * 2]);
        const float p00 = ex2((sv.x - m0) * SC), p01 = ex2((sv.z - m0) * SC);
        const float p10 = ex2((sv.y - m1) * SC), p11 = ex2((sv.w - m1) * SC);
        const int T = tid >> 4, j = tid & 15;
        p_s[((T * 2 + 0) * 4 + (j & 3)) * 4 + (j >> 2)] = pack_bf16(p00, p01);
        p_s[((T * 2 + 1) * 4 + (j & 3)) * 4 + (j >> 2)] = pack_bf16(p10, p11);
        float l0 = p00 + p01, l1 = p10 + p11;
#pragma unroll
        for (int o = 16; o > 0; o >>= 1) {
            l0 += __shfl_xor_sync(0xffffffffu, l0, o);
            l1 += __shfl_xor_sync(0xffffffffu, l1, o);
        }
        if (lane == 0) wsum_s[warp] = make_float2(l0, l1);
        bar_sync(1, 256);
        if (warp == 7 && lane < 4) {
            float l = 0.f;
#pragma unroll
            for (int i = 0; i < 8; i++) l += (lane & 2) ? wsum_s[i].y : wsum_s[i].x;
            st_relaxed(&g_oml[bh][sp * 4 + lane], tagf((lane & 1) ? l : ((lane & 2) ? m1 : m0), tag4));
        }
    }

    {
        float oacc[2][4] = {};
        const uint32_t voff = (warp >> 1) * 4096 + lrow * 128;
        const int c16 = (warp & 1) * 4 + lcol;
        float* op = &g_oval[hkv][(t & 1) * 8 + warp][b * 8 + sp][g + (t >> 1) * 8];
        float fac = 0.f;
        int slot = ST_V % NS;
#pragma unroll 1
        for (int tile = 0; tile < 16; tile++) {
            const int st = ST_V + tile;
            const uint4 pf = *reinterpret_cast<const uint4*>(&p_s[((tile * 2 + (g & 1)) * 4 + t) * 4]);
            if (tile == 15) {
                mbar_wait(fullb + BAR_STAT * 8);
                fac = fac_s[t & 1];
            }
            mbar_wait(fullb + st * 8);
            const uint32_t base = ring + slot * STAGE + voff;
            uint32_t a[2][2][4];
#pragma unroll
            for (int kk = 0; kk < 2; kk++)
#pragma unroll
                for (int mt = 0; mt < 2; mt++)
                    ldsm4t(a[kk][mt], base + kk * 2048 + (((c16 + mt * 2) ^ (lane & 7)) << 4));
            mma16816(oacc[0], a[0][0], pf.x, pf.y);
            mma16816(oacc[1], a[0][1], pf.x, pf.y);
            mma16816(oacc[0], a[1][0], pf.z, pf.w);
            mma16816(oacc[1], a[1][1], pf.z, pf.w);
            __syncwarp();
            if (st < NEMPTY && lane == 0) mbar_arrive(emptyb + st * 8);
            if (++slot == NS) slot = 0;
        }
        st_relaxed(op, tagf(sel4(oacc[0], t) * fac, tag4));
        st_relaxed(op + 16, tagf(sel4(oacc[1], t) * fac, tag4));
    }
    if (tid == 0) TRACE(6);

    if (warp < 7) {
        const int st = ST_WO + (warp >> 2);
        const uint32_t base = ring + (st % NS) * STAGE + (warp & 3) * 4096 + lrow * 128;
        const uint32_t based = ring + (ST_WD % NS) * STAGE + warp * 2048 + lrow * 128;
        float* fp = &g_fbuf[warp * 16 + (g >> 2) + (t >> 1) * 2][cta][(g & 3) * 2 + (t & 1)];
        uint32_t a[2][4][4];
        mbar_wait(fullb + st * 8);
#pragma unroll
        for (int ks = 0; ks < 2; ks++)
#pragma unroll
            for (int mt = 0; mt < 4; mt++)
                ldsm4t(a[ks][mt], base + ks * 2048 + (((mt * 2 + lcol) ^ (lane & 7)) << 4));
        float acc[4][4] = {};
        uint32_t todo = has_ffn ? 3u : 1u;
        unsigned n = 0;
#pragma unroll 1
        while (todo) {
            if ((todo & 1u) && mbar_test(fullb + BAR_O * 8)) {
                if (tid == 32) TRACE(60);
                const uint32_t b00 = oh_s[g & 1][t], b01 = oh_s[g & 1][4 + t];
                const uint32_t b10 = oh_s[g & 1][8 + t], b11 = oh_s[g & 1][12 + t];
#pragma unroll
                for (int mt = 0; mt < 4; mt++) mma16816(acc[mt], a[0][mt], b00, b01);
#pragma unroll
                for (int mt = 0; mt < 4; mt++) mma16816(acc[mt], a[1][mt], b10, b11);
                todo &= ~1u;
            }
            if ((todo & 2u) && mbar_test(fullb + ST_WD * 8) && mbar_test(fullb + BAR_H * 8)) {
                if (tid == 64) TRACE(61);
                const uint32_t b0 = oh_s[g & 1][16 + t], b1 = oh_s[g & 1][20 + t];
#pragma unroll
                for (int mt = 0; mt < 4; mt++) {
                    uint32_t d[4];
                    ldsm4t(d, based + (((mt * 2 + lcol) ^ (lane & 7)) << 4));
                    mma16816(acc[mt], d, b0, b1);
                }
                todo &= ~2u;
            }
            if (++n > SPIN_LIMIT) __trap();
        }
        if (tid == 96 && acc[0][0] != 123.456f) TRACE(62);
#pragma unroll
        for (int mt = 0; mt < 4; mt++) st_relaxed(fp + mt * 4 * NCTA * 8, tagf(sel4(acc[mt], t), tag4));
        if (tid == 0) TRACE(8);
    }
}

typedef CUresult (*EncodeFn)(CUtensorMap*, CUtensorMapDataType, cuuint32_t, void*, const cuuint64_t*,
                             const cuuint64_t*, const cuuint32_t*, const cuuint32_t*, CUtensorMapInterleave,
                             CUtensorMapSwizzle, CUtensorMapL2promotion, CUtensorMapFloatOOBfill);

#define PR_WQ 3
#define PR_KV 3
#define PR_GU 3
#define PR_W 3
void make_3d(EncodeFn enc, CUtensorMap* m, const void* base, uint64_t d0, uint64_t d1, uint64_t d2, uint64_t s1,
             uint64_t s2, uint32_t b0, uint32_t b1, uint32_t b2, CUtensorMapSwizzle sw, int promo) {
    cuuint64_t gd[3] = {d0, d1, d2};
    cuuint64_t gs[2] = {s1, s2};
    cuuint32_t bx[3] = {b0, b1, b2};
    cuuint32_t es[3] = {1, 1, 1};
    enc(m, CU_TENSOR_MAP_DATA_TYPE_BFLOAT16, 3, const_cast<void*>(base), gd, gs, bx, es,
        CU_TENSOR_MAP_INTERLEAVE_NONE, sw, (CUtensorMapL2promotion)promo, CU_TENSOR_MAP_FLOAT_OOB_FILL_NONE);
}

}

extern "C" void kernel_launch(void* const* d_in, const int* in_sizes, int n_in, void* d_out, int out_size) {
    (void)in_sizes; (void)n_in; (void)out_size;
    static EncodeFn enc = nullptr;
    if (!enc) {
        cudaDriverEntryPointQueryResult qr;
        void* fn = nullptr;
        cudaGetDriverEntryPoint("cuTensorMapEncodeTiled", &fn, cudaEnableDefault, &qr);
        enc = (EncodeFn)fn;
        cudaFuncSetAttribute(fused_decode_kernel, cudaFuncAttributeMaxDynamicSharedMemorySize, SMEM_BYTES);
    }
    Maps maps;
    make_3d(enc, &maps.m[0], d_in[3], 4096, 224, 2, 8192, 224 * 8192, 32, 224, 1, CU_TENSOR_MAP_SWIZZLE_64B, PR_WQ);
    make_3d(enc, &maps.m[1], d_in[1], 64, 16 * SK, 4, 512, 128, 64, 32, 4, CU_TENSOR_MAP_SWIZZLE_128B, PR_KV);
    make_3d(enc, &maps.m[2], d_in[2], 64, 16 * SK, 4, 512, 128, 64, 32, 4, CU_TENSOR_MAP_SWIZZLE_128B, PR_KV);
    make_3d(enc, &maps.m[3], d_in[6], 1792, 224, 2, 3584, 224 * 3584, 16, 224, 2, CU_TENSOR_MAP_SWIZZLE_32B, PR_GU);
    make_3d(enc, &maps.m[4], d_in[7], 1792, 224, 2, 3584, 224 * 3584, 16, 224, 2, CU_TENSOR_MAP_SWIZZLE_32B, PR_GU);
    make_3d(enc, &maps.m[5], d_in[4], 64, 4096, 7, 896, 128, 64, 32, 4, CU_TENSOR_MAP_SWIZZLE_128B, PR_W);
    make_3d(enc, &maps.m[6], d_in[8], 64, 1792, 7, 896, 128, 64, 16, 7, CU_TENSOR_MAP_SWIZZLE_128B, PR_W);
    fused_decode_kernel<<<NCTA, NTHREADS, SMEM_BYTES, cudaStreamPerThread>>>(
        maps, (const __nv_bfloat16*)d_in[0], (__nv_bfloat16*)d_out, (const unsigned char*)d_in[3],
        (const unsigned char*)d_in[1]);
}
```

```cpp
#include <cuda_runtime.h>
#include <cuda.h>
#include <cuda_bf16.h>
#include <stdint.h>

namespace clustered {

constexpr int D_MODEL = 448;
constexpr int SK = 32768;
constexpr int WIN = 4096;
constexpr int CL = 16;
constexpr int NCL = 7;
constexpr int NCTA = CL * NCL;
constexpr int STAGE = 16384;
constexpr int NS = 13;
constexpr int NT = 19;
constexpr int ST_K = 2;
constexpr int ST_V = ST_K + NT;
constexpr int ST_G = ST_V + NT;
constexpr int ST_WO = ST_G + 2;
constexpr int ST_WD = ST_WO + 2;
constexpr int NST = ST_WD + 1;
constexpr int NEMPTY = NST - NS;
constexpr int BAR_STAT = NST + NEMPTY;
constexpr int BAR_Q = BAR_STAT + 1;
constexpr int BAR_O = BAR_STAT + 2;
constexpr int BAR_GU = BAR_STAT + 3;
constexpr int BAR_F = BAR_STAT + 4;
constexpr int BAR_X = BAR_STAT + 5;
constexpr int BAR_H = BAR_STAT + 6;
constexpr int NBAR = BAR_STAT + 7;
constexpr int N0 = 4;
constexpr int NTHREADS = 512;
constexpr int LNW = 12;
struct Tune { float t[18]; int s[5]; };
enum { T_K, T_V, T_VE, T_G, T_U, T_WO0, T_WO1, T_WD, T_SKV, T_SG, T_SW, T_Q, T_K0, T_K1, T_HD, T_XKV, T_XW, T_H };
enum { S_Q, S_O, S_OF, S_HF, S_DEPTH };
constexpr Tune g_tune = {{200.f, 10980.f, 21629.f, 21710.f, 22282.f, 22879.f, 23247.f, 23952.f, 579.f, 543.f, 469.f, 3800.f,
                          150.f, 450.f, 200.f, 400.f, 200.f, 24200.f},
                         {1, ST_V + 10, ST_G, ST_WO, 8}};
constexpr unsigned SPIN_LIMIT = 1u << 22;
constexpr unsigned long long EVICT_FIRST = 0x12F0000000000000ull;

constexpr int SM_BAR = NS * STAGE;
constexpr int SM_SCHED = SM_BAR + (NBAR * 8 + 15) / 16 * 16;
constexpr int SM_S = SM_SCHED + NST * 16;
constexpr int SM_P = SM_S + NT * 256;
constexpr int SM_Q = SM_P + (NT + 4) * 128;
constexpr int SM_O = SM_Q + 1152;
constexpr int SM_H = SM_O + 1152;
constexpr int SM_GU = SM_H + 640;
constexpr int SM_F = SM_GU + 3584;
constexpr int SM_W = SM_F + 1024;
constexpr int SMEM_BYTES = SM_W + 144;
static_assert(SMEM_BYTES <= 232448, "smem map");

struct Scratch {
    float part[2][16][2][NCL][256];
    float oml[16][32];
    unsigned int hbuf[NCTA][32];
    unsigned int epoch[NCTA];
};
__device__ __align__(128) Scratch g_scratch;

__device__ __forceinline__ uint32_t globaltimer_lo() {
    uint32_t t;
    asm volatile("mov.u32 %0, %globaltimer_lo;" : "=r"(t));
    return t;
}
__device__ __forceinline__ uint32_t globaltimer_v() {
    unsigned long long t;
    asm volatile("mov.u64 %0, %globaltimer;" : "=l"(t));
    return (uint32_t)t;
}
__device__ __forceinline__ uint32_t smem_u32(const void* p) {
    return (uint32_t)__cvta_generic_to_shared(p);
}
__device__ __forceinline__ void mbar_init(uint32_t bar, uint32_t cnt) {
    asm volatile("mbarrier.init.shared::cta.b64 [%0], %1;" ::"r"(bar), "r"(cnt) : "memory");
}
__device__ __forceinline__ void mbar_expect_tx(uint32_t bar, uint32_t bytes) {
    asm volatile("mbarrier.arrive.expect_tx.shared::cta.b64 _, [%0], %1;" ::"r"(bar), "r"(bytes) : "memory");
}
__device__ __forceinline__ void mbar_arrive(uint32_t bar) {
    asm volatile("mbarrier.arrive.shared::cta.b64 _, [%0];" ::"r"(bar) : "memory");
}
__device__ __forceinline__ void mbar_wait(uint32_t bar) {
    unsigned n = 0;
    uint32_t ok;
    do {
        asm volatile(
            "{\n.reg .pred p;\n"
            "mbarrier.try_wait.parity.shared::cta.b64 p, [%1], 0;\n"
            "selp.u32 %0, 1, 0, p;\n}"
            : "=r"(ok) : "r"(bar) : "memory");
        if (++n > SPIN_LIMIT) __trap();
    } while (!ok);
}
__device__ __forceinline__ void mbar_nap(uint32_t bar, uint32_t ns) {
    asm volatile(
        "{\n.reg .pred p;\n"
        "mbarrier.try_wait.parity.shared::cta.b64 p, [%0], 0, %1;\n}"
        ::"r"(bar), "r"(ns) : "memory");
}
__device__ __forceinline__ uint32_t mbar_test(uint32_t bar) {
    uint32_t ok;
    asm volatile(
        "{\n.reg .pred p;\n"
        "mbarrier.test_wait.parity.shared::cta.b64 p, [%1], 0;\n"
        "selp.u32 %0, 1, 0, p;\n}"
        : "=r"(ok) : "r"(bar) : "memory");
    return ok;
}
__device__ __forceinline__ void tma_3d(uint32_t dst, const void* m, int c0, int c1, int c2, uint32_t bar) {
    asm volatile(
        "cp.async.bulk.tensor.3d.shared::cluster.global.mbarrier::complete_tx::bytes.L2::cache_hint"
        " [%0], [%1, {%3, %4, %5}], [%2], %6;"
        ::"r"(dst), "l"(m), "r"(bar), "r"(c0), "r"(c1), "r"(c2), "l"(EVICT_FIRST) : "memory");
}
__device__ __forceinline__ void prefetch_map(const CUtensorMap* m) {
    asm volatile("prefetch.tensormap [%0];" ::"l"(m) : "memory");
}
__device__ __forceinline__ void ldsm4(uint32_t (&a)[4], uint32_t addr) {
    asm volatile("ldmatrix.sync.aligned.m8n8.x4.shared.b16 {%0,%1,%2,%3}, [%4];"
                 : "=r"(a[0]), "=r"(a[1]), "=r"(a[2]), "=r"(a[3]) : "r"(addr) : "memory");
}
__device__ __forceinline__ void ldsm4t(uint32_t (&a)[4], uint32_t addr) {
    asm volatile("ldmatrix.sync.aligned.m8n8.x4.trans.shared.b16 {%0,%1,%2,%3}, [%4];"
                 : "=r"(a[0]), "=r"(a[1]), "=r"(a[2]), "=r"(a[3]) : "r"(addr) : "memory");
}
__device__ __forceinline__ void mma16816(float (&c)[4], const uint32_t (&a)[4], uint32_t b0, uint32_t b1) {
    asm volatile(
        "mma.sync.aligned.m16n8k16.row.col.f32.bf16.bf16.f32 {%0,%1,%2,%3}, {%4,%5,%6,%7}, {%8,%9}, {%0,%1,%2,%3};"
        : "+f"(c[0]), "+f"(c[1]), "+f"(c[2]), "+f"(c[3])
        : "r"(a[0]), "r"(a[1]), "r"(a[2]), "r"(a[3]), "r"(b0), "r"(b1));
}
__device__ __forceinline__ void bar_sync(int id, int n) {
    asm volatile("bar.sync %0, %1;" ::"r"(id), "r"(n) : "memory");
}
__device__ __forceinline__ float bf16r(float x) { return __bfloat162float(__float2bfloat16_rn(x)); }
__device__ __forceinline__ uint32_t pack_bf16(float lo, float hi) {
    __nv_bfloat162 v = __floats2bfloat162_rn(lo, hi);
    return *reinterpret_cast<uint32_t*>(&v);
}
__device__ __forceinline__ float ex2(float x) {
    float y;
    asm("ex2.approx.ftz.f32 %0, %1;" : "=f"(y) : "f"(x));
    return y;
}
__device__ __forceinline__ void st_relaxed(void* p, uint32_t v) {
    asm volatile("st.relaxed.gpu.global.u32 [%0], %1;" ::"l"(p), "r"(v) : "memory");
}
__device__ __forceinline__ void post_or(void* p, uint32_t v) {
    asm volatile("red.relaxed.gpu.global.or.b32 [%0], %1;" ::"l"(p), "r"(v) : "memory");
}
__device__ __forceinline__ uint32_t ld_relaxed(const void* p) {
    uint32_t v;
    asm volatile("ld.relaxed.gpu.global.u32 %0, [%1];" : "=r"(v) : "l"(p) : "memory");
    return v;
}
__device__ __forceinline__ uint32_t ld_nc(const void* p) {
    uint32_t v;
    asm volatile("ld.global.nc.u32 %0, [%1];" : "=r"(v) : "l"(p) : "memory");
    return v;
}
__device__ __forceinline__ void ld_relaxed4_if(uint4& v, const void* p, uint32_t pred) {
    asm volatile("{\n.reg .pred p;\nsetp.ne.u32 p, %5, 0;\n@p ld.relaxed.gpu.global.v4.u32 {%0,%1,%2,%3}, [%4];\n}"
                 : "+r"(v.x), "+r"(v.y), "+r"(v.z), "+r"(v.w) : "l"(p), "r"(pred) : "memory");
}
__device__ __forceinline__ void ld_relaxed_if(uint32_t& v, const void* p, uint32_t pred) {
    asm volatile("{\n.reg .pred p;\nsetp.ne.u32 p, %2, 0;\n@p ld.relaxed.gpu.global.u32 %0, [%1];\n}"
                 : "+r"(v) : "l"(p), "r"(pred) : "memory");
}
__device__ __forceinline__ uint32_t tagf(float v, uint32_t tag4) { return (__float_as_uint(v) & ~15u) | tag4; }
__device__ __forceinline__ float sel4(const float (&c)[4], int t) {
    float lo = (t & 1) ? c[1] : c[0];
    float hi = (t & 1) ? c[3] : c[2];
    return (t & 2) ? hi : lo;
}

__device__ __forceinline__ uint32_t mapa(uint32_t addr, uint32_t rank) {
    uint32_t r;
    asm volatile("mapa.shared::cluster.u32 %0, %1, %2;" : "=r"(r) : "r"(addr), "r"(rank));
    return r;
}
__device__ __forceinline__ void st_async2(uint32_t addr, float v0, float v1, uint32_t bar) {
    asm volatile("st.async.shared::cluster.mbarrier::complete_tx::bytes.v2.f32 [%0], {%1, %2}, [%3];"
                 ::"r"(addr), "f"(v0), "f"(v1), "r"(bar) : "memory");
}
__device__ __forceinline__ uint4 lds128(uint32_t a) {
    uint4 v;
    asm volatile("ld.shared.v4.u32 {%0,%1,%2,%3}, [%4];" : "=r"(v.x), "=r"(v.y), "=r"(v.z), "=r"(v.w) : "r"(a) : "memory");
    return v;
}

struct Maps {
    CUtensorMap m[6];
};

__global__ void __launch_bounds__(NTHREADS, 1)
fused_decode_kernel(const __nv_bfloat16* __restrict__ x, __nv_bfloat16* __restrict__ out, Scratch* __restrict__ sc,
                    const uint4* __restrict__ wq, const __grid_constant__ Maps maps,
                    const __grid_constant__ Tune tn) {
    extern __shared__ __align__(1024) unsigned char smem[];
    const int tid = threadIdx.x;
    const int cta = blockIdx.x;
    const int rk = cta & 15;
    const int cl = cta >> 4;
    const uint32_t ring = smem_u32(smem);
    const uint32_t fullb = ring + SM_BAR;
    const int kvrow = rk * SK + (SK - WIN) + cl * 32;
    {
        const int r = tid >> 5, c = tid & 31;
        const uint32_t d = ring + (c >> 3) * 4096 + r * 128 + (((c & 7) ^ r) << 4);
        const uint4* p = wq + (tid + r * 480 + cta * 32 + cl * 32256);
        asm volatile("{\n.reg .pred p;\nsetp.lt.u32 p, %3, 256;\n"
                     "@p cp.async.cg.shared.global.L2::cache_hint.L2::128B [%0], [%1], 16, %2;\n}"
                     ::"r"(d), "l"(p), "l"(EVICT_FIRST), "r"(tid) : "memory");
        if (tid < 256) {
#pragma unroll
            for (int i = 1; i < 8; i++) {
                p += 4096;
                asm volatile("" : "+l"(p));
                asm volatile("cp.async.cg.shared.global.L2::cache_hint.L2::128B [%0], [%1], 16, %2;"
                             ::"r"(d + (i >> 2) * STAGE + (i & 3) * 1024), "l"(p), "l"(EVICT_FIRST) : "memory");
            }
        }
    }
    uint32_t xr[10];
    if (tid >= LNW * 32 && tid < LNW * 32 + 64) {
        xr[9] = ld_relaxed(&sc->epoch[cta]);
        const uint32_t* xp = reinterpret_cast<const uint32_t*>(x) + ((tid >> 5) - LNW) * 224;
#pragma unroll
        for (int i = 0; i < 7; i++) xr[i] = ld_nc(xp + (tid & 31) + 32 * i);
        xr[7] = ld_nc(xp + cl * 32 + (tid & 31));
        xr[8] = ld_nc(xp + min(rk, 13) * 16 + (tid & 15));
    }
    const uint32_t t0 = globaltimer_lo();
    int4* sched_s = reinterpret_cast<int4*>(smem + SM_SCHED);
    float2* s_s = reinterpret_cast<float2*>(smem + SM_S);
    uint32_t* p_s = reinterpret_cast<uint32_t*>(smem + SM_P);
    float2* wmax_s = reinterpret_cast<float2*>(smem + SM_W);
    float2* wsum_s = wmax_s + 8;
    float* fac_s = reinterpret_cast<float*>(wmax_s + 16);

    const int warp = tid >> 5;
    const int lane = tid & 31;
    const uint32_t emptyb = fullb + NST * 8;
    const unsigned mv = (unsigned)(cl + 35 - 2 * rk);
    const int m7 = (int)(mv - 7u * ((mv * 37u) >> 8));
    const int x0 = m7 == 0 ? cl : -1;
    const int ntile = m7 < 2 ? NT : NT - 1;
    const bool has_gu = rk < 14;

    if (lane == 0 && warp >= 8 && warp != LNW && warp != LNW + 1) {
        if (warp == 8) {
            prefetch_map(&maps.m[0]);
            mbar_init(fullb, 256);
            mbar_init(fullb + 8, 256);
#pragma unroll
            for (int i = ST_K; i < 14; i++) mbar_init(fullb + i * 8, 1);
        } else if (warp == 9) {
            prefetch_map(&maps.m[1]);
#pragma unroll
            for (int i = 14; i < 30; i++) mbar_init(fullb + i * 8, 1);
        } else if (warp == 10) {
            prefetch_map(&maps.m[2]);
#pragma unroll
            for (int i = 30; i < NST; i++) mbar_init(fullb + i * 8, 1);
        } else if (warp == 11) {
            prefetch_map(&maps.m[3]);
#pragma unroll
            for (int i = ST_K; i < ST_V; i++) mbar_init(emptyb + i * 8, 1);
        } else if (warp == 14) {
            prefetch_map(&maps.m[4]);
#pragma unroll
            for (int i = 0; i < NEMPTY; i++)
                if (i < ST_K || i >= ST_V) mbar_init(emptyb + i * 8, 8);
        } else {
            prefetch_map(&maps.m[5]);
#pragma unroll
            for (int i = BAR_STAT; i < NBAR; i++)
                mbar_init(fullb + i * 8, (i == BAR_O || i == BAR_Q) ? 4 : i == BAR_X ? 2 : 1);
            mbar_expect_tx(fullb + BAR_GU * 8, 3584);
            mbar_expect_tx(fullb + BAR_F * 8, 1024);
            mbar_expect_tx(fullb + BAR_H * 8, 1);
        }
        asm volatile("fence.proxy.async.shared::cta;" ::: "memory");
        asm volatile("fence.mbarrier_init.release.cluster;" ::: "memory");
    }
    __syncthreads();
    if (tid < 256) {
        asm volatile("cp.async.mbarrier.arrive.noinc.shared::cta.b64 [%0];" ::"r"(fullb) : "memory");
        asm volatile("cp.async.mbarrier.arrive.noinc.shared::cta.b64 [%0];" ::"r"(fullb + 8) : "memory");
    }
    asm volatile("barrier.cluster.arrive.relaxed.aligned;" ::: "memory");

    if (warp == 9) {
#pragma unroll 1
        for (int i = lane; i < NST; i += 32) {
            const float rn = 1.f / (float)ntile;
            const int xrow = rk * SK + (SK - WIN) + (cl == x0 ? 126 : 127) * 32;
            int map, bytes = STAGE, c1, c2 = 0;
            float u, sg = tn.t[T_SKV];
            if (i < ST_G) {
                const bool isv = i >= ST_V;
                const int j = isv ? ST_G - 1 - i : i - ST_K;
                map = isv ? 1 : 0;
                c1 = j < NT - 1 ? kvrow + j * 224 : xrow;
                if (j >= ntile) bytes = 0;
                u = isv ? tn.t[T_V] + (tn.t[T_VE] - tn.t[T_V]) * rn * (float)max(ntile - 1 - j, 0)
                        : tn.t[T_K] + (tn.t[T_V] - tn.t[T_K]) * rn * (float)j;
            } else {
                u = tn.t[T_G + i - ST_G];
                if (i < ST_WO) {
                    map = 2 + i - ST_G; c1 = rk * 32; c2 = cl * 4;
                    if (!has_gu) bytes = 0;
                    sg = tn.t[T_SG];
                } else {
                    c2 = cl;
                    sg = tn.t[T_SW];
                    if (i < ST_WD) {
                        map = 4; c1 = rk * 256 + (i - ST_WO) * 128;
                    } else {
                        map = 5; c1 = rk * 112; bytes = 14336;
                    }
                }
            }
            u += sg * ((float)(rk * 7 + cl) * (1.f / 112.f) - 0.5f);
            const int tm = u > 0.f ? (int)u : 0;
            sched_s[i] = make_int4((map * 128) | (bytes << 16), c1, c2, ((i - tn.s[S_DEPTH]) & 0xffff) | (tm << 16));
        }
        __syncwarp();
        asm volatile("bar.arrive 2, 64;" ::: "memory");
    }
    if (warp == 8) {
        if (lane == 0) {
#pragma unroll 1
            for (int i = ST_K; i < N0; i++) {
                const uint32_t tm = (uint32_t)tn.t[T_K0 + i - ST_K];
                unsigned n = 0;
                while (globaltimer_lo() - t0 < tm && ++n < 4096u) {}
                mbar_expect_tx(fullb + i * 8, STAGE);
                tma_3d(ring + i * STAGE, &maps.m[0], 0, kvrow + (i - ST_K) * 224, 0, fullb + i * 8);
            }
        }
        __syncwarp();
        bar_sync(2, 64);
        if (lane == 0) {
            int slot = N0;
            const int xkv = (int)tn.t[T_XKV], xw = (int)tn.t[T_XW];
#pragma unroll 1
            for (int i = N0; i < NST; i++) {
                if (i == ST_V - 1 && ntile < NT) {
                    mbar_arrive(fullb + (ST_V - 1) * 8);
                    mbar_arrive(fullb + ST_V * 8);
                    i = ST_V + 1;
                    slot = (ST_V + 1) % NS;
                }
                const int4 e = sched_s[i];
                if (!(e.w & 0x8000)) mbar_wait(fullb + (e.w & 0xff) * 8);
                if (i >= NS) mbar_wait(emptyb + (i - NS) * 8);
                {
                    const uint32_t tm = (uint32_t)e.w >> 16;
                    const uint32_t te = (uint32_t)max((int)tm - (i < ST_WO ? xkv : xw), 0);
                    unsigned n = 0;
                    while (true) {
                        const uint32_t now = globaltimer_v() - t0;
                        if (now >= tm || ++n >= 4096u) break;
                        if (now >= te && mbar_test(fullb + (i - 2) * 8)) break;
                    }
                }
                const uint32_t bytes = (uint32_t)e.x >> 16;
                mbar_expect_tx(fullb + i * 8, bytes);
                if (bytes)
                    tma_3d(ring + slot * STAGE, reinterpret_cast<const unsigned char*>(&maps) + (e.x & 0xffff), 0, e.y,
                           e.z, fullb + i * 8);
                if (++slot == NS) slot = 0;
            }
        }
        return;
    }

    if (warp == LNW || warp == LNW + 1) {
        float v[14];
        float s = 0.f;
#pragma unroll
        for (int i = 0; i < 7; i++) {
            v[2 * i] = __uint_as_float(xr[i] << 16);
            v[2 * i + 1] = __uint_as_float(xr[i] & 0xffff0000u);
            s += v[2 * i] + v[2 * i + 1];
        }
#pragma unroll
        for (int o = 16; o > 0; o >>= 1) s += __shfl_xor_sync(0xffffffffu, s, o);
        const float mean = s * (1.0f / D_MODEL);
        float ss = 0.f;
#pragma unroll
        for (int i = 0; i < 14; i++) ss += (v[i] - mean) * (v[i] - mean);
#pragma unroll
        for (int o = 16; o > 0; o >>= 1) ss += __shfl_xor_sync(0xffffffffu, ss, o);
        const float mb = bf16r(mean);
        const float var = bf16r(ss * (1.0f / D_MODEL));
        const float rsd = __frcp_rn(bf16r(__fsqrt_rn(bf16r(var + 1e-5f))));
        const int o = (lane >> 4) * 32 + ((warp - LNW) * 4 + (lane & 3)) * 4 + ((lane >> 2) & 3);
#pragma unroll
        for (int i = 0; i < 2; i++)
            p_s[i * (NT + 2) * 32 + o] = pack_bf16(bf16r(__uint_as_float(xr[7 + i] << 16) - mb) * rsd,
                                                   bf16r(__uint_as_float(xr[7 + i] & 0xffff0000u) - mb) * rsd);
        if (tid == LNW * 32) {
            reinterpret_cast<uint32_t*>(fac_s)[2] = xr[9];
            sc->epoch[cta] = xr[9] + 1;
            reinterpret_cast<uint32_t*>(fac_s)[3] = (xr[9] % 15u) + 1u;
        }
        __syncwarp();
        if (lane == 0) mbar_arrive(fullb + BAR_X * 8);
    }
    uint32_t epoch = 0;
    if (warp > 8) {
        mbar_wait(fullb + BAR_X * 8);
        epoch = reinterpret_cast<volatile uint32_t*>(fac_s)[2];
    }
    const uint32_t tag16 = (epoch % 65535u) + 1u;
    const uint32_t tag4 = (epoch % 15u) + 1u;
    const int g = lane >> 2;
    const int t = lane & 3;
    const float SC = 0.0625f * 1.4426950408889634f;

    if (warp >= 12) {
        const int j = tid - 384;
        const int q = j & 63;
#pragma unroll 1
        for (int pass = 0; pass < 2; pass++) {
            const float* ib = &sc->part[pass][rk][j >> 6][0][q * 4];
            uint32_t* os = reinterpret_cast<uint32_t*>(smem + SM_Q + pass * 1152) + ((j >> 6) * 4 + (q & 1) * 2) * 36 +
                           (q >> 2) * 2 + ((q >> 1) & 1);
            const uint32_t fastb = fullb + tn.s[pass ? S_OF : S_Q] * 8;
            mbar_wait(fullb + tn.s[pass ? S_O : S_Q] * 8);
            {
                const uint32_t tm = (uint32_t)tn.t[T_Q];
                unsigned k = 0;
                while (globaltimer_lo() - t0 < tm && ++k < 4096u) __nanosleep(40);
            }
            uint4 w[7] = {};
            uint32_t pend = 127u;
            unsigned n = 0;
            while (true) {
#pragma unroll
                for (int s = 0; s < 7; s++) ld_relaxed4_if(w[s], ib + s * 256, pend & (1u << s));
                pend = 0;
#pragma unroll
                for (int s = 0; s < 7; s++)
                    if (((w[s].x ^ tag4) | (w[s].y ^ tag4) | (w[s].z ^ tag4) | (w[s].w ^ tag4)) & 15u) pend |= 1u << s;
                if (!__any_sync(0xffffffffu, pend)) break;
                if (++n > SPIN_LIMIT) __trap();
                mbar_nap(fastb, 4000);
            }
            float a[4] = {};
#pragma unroll
            for (int s = 0; s < 7; s++) {
                a[0] += __uint_as_float(w[s].x);
                a[1] += __uint_as_float(w[s].y);
                a[2] += __uint_as_float(w[s].z);
                a[3] += __uint_as_float(w[s].w);
            }
            os[0] = pack_bf16(a[0], a[1]);
            os[36] = pack_bf16(a[2], a[3]);
            __syncwarp();
            if (lane == 0) mbar_arrive(fullb + (BAR_Q + pass) * 8);
        }
    }
    if (warp == 9) {
        uint32_t gu = ring + SM_GU + lane * 8;
        unsigned int* hp = &sc->hbuf[cta][lane];
        asm volatile("" : "+r"(gu));
        st_relaxed(hp, 0u);
#pragma unroll 1
        for (int pass = 0; pass < 2; pass++) {
            if (pass) {
                mbar_wait(fullb + ST_G * 8);
                mbar_wait(fullb + BAR_GU * 8);
            }
            float gs[2] = {}, us[2] = {};
#pragma unroll
            for (int s = 0; s < 14; s++) {
                float vx, vy;
                asm volatile("ld.shared.v2.f32 {%0,%1}, [%2];" : "=f"(vx), "=f"(vy) : "r"(gu + s * 256) : "memory");
                gs[s & 1] += vx;
                us[s & 1] += vy;
            }
            const uint32_t pk = pack_bf16(gs[0] + gs[1], us[0] + us[1]);
            const float hv = __uint_as_float(pk << 16) * __uint_as_float(pk & 0xffff0000u);
            const uint32_t word = __byte_perm(pack_bf16(hv, hv), tag16, 0x5410);
            asm volatile("{\n.reg .pred p;\nsetp.ne.u32 p, %2, 0;\n@p red.relaxed.gpu.global.or.b32 [%0], %1;\n}"
                         ::"l"(hp), "r"(word), "r"(pass) : "memory");
        }
    }
    if (warp > 8 && warp != 11) {
        if (!((0x3400 >> warp) & 1)) return;
        const unsigned int* hp = &sc->hbuf[rk * 7][lane];
        unsigned short* hs = reinterpret_cast<unsigned short*>(smem + SM_H) + (lane >> 2) * 40 + (lane & 3);
        hs[28] = 0;
        uint32_t v[7] = {};
        uint32_t pend = 127u;
        unsigned n = 0;
        {
            mbar_wait(fullb + (ST_G + 1) * 8);
            const uint32_t hb = fullb + (warp >= 12 ? BAR_H : tn.s[S_HF]) * 8;
            const int dl = warp >= 12 ? (int)tn.t[T_H] + (warp - 12) * (int)tn.t[T_HD] : 1000000;
            unsigned k = 0;
            while (++k < 4096u) {
                const int left = dl - (int)(globaltimer_v() - t0);
                if (left <= 0) break;
                mbar_nap(hb, (uint32_t)left);
                if (mbar_test(hb)) break;
            }
        }
        while (true) {
#pragma unroll
            for (int s = 0; s < 7; s++) ld_relaxed_if(v[s], hp + s * 32, pend & (1u << s));
            pend = 0;
#pragma unroll
            for (int s = 0; s < 7; s++) {
                if ((v[s] >> 16) == tag16) hs[s * 4] = (unsigned short)v[s];
                else pend |= 1u << s;
            }
            if (!__any_sync(0xffffffffu, pend)) break;
            if (++n > SPIN_LIMIT) __trap();
        }
        __syncwarp();
        if (lane == 0) {
            asm volatile("fence.acq_rel.cta;" ::: "memory");
            asm volatile("mbarrier.complete_tx.relaxed.cta.shared::cta.b64 [%0], 1;" ::"r"(fullb + BAR_H * 8) : "memory");
        }
        return;
    }
    if (warp == 11) {
        const int oidx = (t >> 1) * D_MODEL + cl * 64 + rk * 4 + (t & 1) * 2;
        const uint32_t xw = *reinterpret_cast<const uint32_t*>(x + oidx);
        const float xa = __uint_as_float(xw << 16), xb = __uint_as_float(xw & 0xffff0000u);
        const float* fs = reinterpret_cast<const float*>(smem + SM_F) + t * 8 + g;
        __nv_bfloat16* op = out + oidx;
#pragma unroll 1
        for (int pass = 0; pass < 2; pass++) {
            if (pass) {
                uint32_t sw;
                unsigned n = 0;
                while (true) {
                    sw = ld_relaxed(&sc->oml[rk][lane]);
                    if (__all_sync(0xffffffffu, (sw & 15u) == tag4 || lane >= 28)) break;
                    if (++n > SPIN_LIMIT) __trap();
                    __nanosleep(500);
                }
                const float val = lane >= 28 ? ((lane & 1) ? 0.f : -INFINITY) : __uint_as_float(sw & ~15u);
                const float ms = __shfl_sync(0xffffffffu, val, lane & ~1);
                float mm = ms;
#pragma unroll
                for (int o = 4; o < 32; o <<= 1) mm = fmaxf(mm, __shfl_xor_sync(0xffffffffu, mm, o));
                float den = val * ex2((ms - mm) * SC);
                if (!(lane & 1)) den = 0.f;
#pragma unroll
                for (int o = 4; o < 32; o <<= 1) den += __shfl_xor_sync(0xffffffffu, den, o);
                if ((lane >> 2) == cl && (lane & 1)) fac_s[(lane >> 1) & 1] = __fdividef(ex2((ms - mm) * SC), den);
                __syncwarp();
                if (lane == 0) mbar_arrive(fullb + BAR_STAT * 8);
                mbar_wait(fullb + (ST_WO + 1) * 8);
                mbar_wait(fullb + BAR_F * 8);
            }
            const float a0 = fs[0] + fs[32], a1 = fs[64] + fs[96], a2 = fs[128] + fs[160], a3 = fs[192] + fs[224];
            const float a = (a0 + a1) + (a2 + a3);
            const uint32_t hi = __float_as_uint(a) & 0xffffe000u;
            const uint32_t lo = __float_as_uint(a - __uint_as_float(hi));
            float c[4];
            asm volatile("mma.sync.aligned.m16n8k8.row.col.f32.tf32.tf32.f32 {%0,%1,%2,%3}, {%4,%4,%4,%4}, {%5,%6}, "
                         "{%7,%8,%7,%8};"
                         : "=f"(c[0]), "=f"(c[1]), "=f"(c[2]), "=f"(c[3])
                         : "r"(0x3f800000u), "r"(hi), "r"(lo), "f"(xa), "f"(xb));
            asm volatile("{\n.reg .pred p;\nsetp.ne.u32 p, %2, 0;\n@p st.global.u32 [%0], %1;\n}"
                         ::"l"(op), "r"(pack_bf16(c[0], c[1])), "r"((int)(pass && lane < 4)) : "memory");
        }
        return;
    }

    const int lrow = (lane & 7) + ((lane >> 4) << 3);
    const int lcol = (lane >> 3) & 1;
    const int frow = (g & 1) * 4 + t;
#pragma unroll 1
    for (int seg = 0; seg < 2; seg++) {
        {
            const int c16 = (warp & 1) * 4 + lcol;
            uint32_t va0 = ring + (warp >> 1) * 4096 + lrow * 128 + ((c16 ^ (lane & 7)) << 4);
            uint32_t va1 = ring + (warp >> 1) * 4096 + lrow * 128 + (((c16 + 2) ^ (lane & 7)) << 4);
            float acc[2][4] = {};
            float g0 = 0.f, g1 = 0.f;
            int st = seg == 0 ? 0 : ST_G - ntile;
            const int ste = seg == 0 ? ST_K : has_gu ? ST_WO : ST_G;
            const int stp = seg == 0 ? ST_K - 1 : ST_G - 1;
            int slot = st % NS;
            uint32_t pa = ring + SM_P + (seg == 0 ? 0 : st - NT) * 128 + frow * 16;
            float* op = seg == 0 ? &sc->part[0][(t & 1) * 8 + (rk >> 1)][rk & 1][cl][warp * 32 + g + (t >> 1) * 8]
                                 : &sc->part[1][(rk & 7) * 2 + (t & 1)][rk >> 3][cl][warp * 32 + g + (t >> 1) * 8];
            const uint32_t gloc = ring + SM_GU + rk * 256 + (((t & 1) * 4 + (g >> 1)) * 4 + (t >> 1) * 2 + (g & 1)) * 8;
            uint32_t gd0 = mapa(gloc, warp * 2), gb0 = mapa(fullb + BAR_GU * 8, warp * 2);
            uint32_t gd1 = mapa(gloc, warp * 2 + 1), gb1 = mapa(fullb + BAR_GU * 8, warp * 2 + 1);
            asm volatile("" : "+r"(gd0), "+r"(gb0), "+r"(gd1), "+r"(gb1), "+r"(va0), "+r"(va1), "+l"(op));
            float fac = 1.f;
            st_relaxed(op, 0u);
            st_relaxed(op + 16, 0u);
            if (seg == 0 && warp == 7 && lane < 4) st_relaxed(&sc->oml[rk][cl * 4 + lane], 0u);
            mbar_wait(fullb + BAR_X * 8);
            const uint32_t tag4 = reinterpret_cast<volatile uint32_t*>(fac_s)[3];
#pragma unroll 1
            for (; st < ste; st++) {
                const uint4 pf = lds128(pa);
                if (st == ST_G - 1) {
                    mbar_wait(fullb + BAR_STAT * 8);
                    fac = fac_s[t & 1];
                }
                mbar_wait(fullb + st * 8);
                uint32_t a[2][2][4];
                ldsm4t(a[0][0], va0 + slot * STAGE);
                ldsm4t(a[0][1], va1 + slot * STAGE);
                ldsm4t(a[1][0], va0 + slot * STAGE + 2048);
                ldsm4t(a[1][1], va1 + slot * STAGE + 2048);
                mma16816(acc[0], a[0][0], pf.x, pf.y);
                mma16816(acc[1], a[0][1], pf.x, pf.y);
                mma16816(acc[0], a[1][0], pf.z, pf.w);
                mma16816(acc[1], a[1][1], pf.z, pf.w);
                __syncwarp();
                if (st < NEMPTY && lane == 0) mbar_arrive(emptyb + st * 8);
                if (++slot == NS) slot = 0;
                pa += 128;
                if (st >= stp) {
                    const float r0 = sel4(acc[0], t), r1 = sel4(acc[1], t);
                    if (st == ST_G + 1) {
                        st_async2(gd0, g0, r0, gb0);
                        st_async2(gd1, g1, r1, gb1);
                    } else if (st == stp) {
                        post_or(op, tagf(r0 * fac, tag4));
                        post_or(op + 16, tagf(r1 * fac, tag4));
                    }
                    g0 = r0;
                    g1 = r1;
#pragma unroll
                    for (int i = 0; i < 4; i++) acc[0][i] = acc[1][i] = 0.f;
                }
            }
        }
        {
            const uint32_t dry = seg == 0;
            const int mt = warp & 3, kh = warp >> 2;
            const uint32_t sw = lrow * 128 + (((mt * 2 + lcol) ^ (lane & 7)) << 4);
            uint32_t base = ring + ((ST_WO + kh) % NS) * STAGE + sw;
            uint32_t based = ring + (ST_WD % NS) * STAGE + kh * 8192 + sw;
            uint32_t based3 = based + (kh ? 2 : 3) * 2048;
            const int brow = ((g >> 1) & 1) * 4 + t;
            uint32_t oa = ring + SM_O + brow * 144 + kh * 64;
            uint32_t ha = ring + SM_H + brow * 80 + kh * 32;
            const int dest = mt * 4 + (g >> 2) + (t >> 1) * 2;
            uint32_t fdst = mapa(ring + SM_F + (rk * 2 + kh) * 32 + ((t & 1) * 4 + (g & 3)) * 4, dest);
            uint32_t fbar = mapa(fullb + BAR_F * 8, dest);
            uint32_t bo = fullb + (dry ? 0 : BAR_O * 8), bw = fullb + (dry ? 0 : (ST_WO + kh) * 8);
            uint32_t bh = fullb + (dry ? 0 : BAR_H * 8), bd = fullb + (dry ? 0 : ST_WD * 8);
            asm volatile("" : "+r"(base), "+r"(based), "+r"(based3), "+r"(oa), "+r"(ha), "+r"(fdst), "+r"(fbar),
                              "+r"(bo), "+r"(bw), "+r"(bh), "+r"(bd));
            float acc[4][4] = {};
            {
                uint32_t a[8][4];
                uint4 bf[4];
                mbar_wait(bo);
#pragma unroll
                for (int k2 = 0; k2 < 4; k2++) bf[k2] = lds128(oa + k2 * 16);
                mbar_wait(bw);
#pragma unroll
                for (int ks = 0; ks < 8; ks++) ldsm4t(a[ks], base + ks * 2048);
#pragma unroll
                for (int k2 = 0; k2 < 4; k2++) {
                    mma16816(acc[(k2 & 1) * 2], a[k2 * 2], bf[k2].x, bf[k2].y);
                    mma16816(acc[(k2 & 1) * 2 + 1], a[k2 * 2 + 1], bf[k2].z, bf[k2].w);
                }
            }
            uint32_t d[4][4];
            mbar_wait(bh);
            const uint4 h0 = lds128(ha), h1 = lds128(ha + 16);
            mbar_wait(bd);
#pragma unroll
            for (int ks = 0; ks < 3; ks++) ldsm4t(d[ks], based + ks * 2048);
            ldsm4t(d[3], based3);
            mma16816(acc[0], d[0], h0.x, h0.y);
            mma16816(acc[1], d[1], h0.z, h0.w);
            mma16816(acc[2], d[2], h1.x, h1.y);
            mma16816(acc[3], d[3], h1.z, h1.w);
            const bool up = t >> 1;
            const float res = (((up ? acc[0][2] : acc[0][0]) + (up ? acc[1][2] : acc[1][0])) + (up ? acc[2][2] : acc[2][0])) +
                              (up ? acc[3][2] : acc[3][0]);
            asm volatile("{\n.reg .pred p;\nsetp.eq.u32 p, %3, 0;\n"
                         "@p st.async.shared::cluster.mbarrier::complete_tx::bytes.f32 [%0], %1, [%2];\n}"
                         ::"r"(fdst), "f"(res), "r"(fbar), "r"(dry) : "memory");
            if (!dry) {
                return;
            }
        }

        {
            uint4 qf[8];
            mbar_wait(fullb + BAR_Q * 8);
#pragma unroll
            for (int k2 = 0; k2 < 8; k2++) qf[k2] = lds128(ring + SM_Q + frow * 144 + k2 * 16);
            float mx0 = -INFINITY, mx1 = -INFINITY;
            const uint32_t koff = ((lane & 7) + ((lane >> 3) & 1) * 8) * 128;
#pragma unroll 1
            for (int tile = warp; tile < NT; tile += 8) {
                const int st = ST_K + tile;
                float e0 = -INFINITY, e1 = -INFINITY;
                const int mt = t >> 1;
                if (tile < ntile) {
                    mbar_wait(fullb + st * 8);
                    const uint32_t base = ring + (st % NS) * STAGE + koff;
                    float acc[2][2][4] = {};
#pragma unroll
                    for (int ks = 0; ks < 16; ks++) {
                        const uint32_t off = (ks >> 2) * 4096 + ((((ks & 3) * 2 + (lane >> 4)) ^ (lane & 7)) << 4);
#pragma unroll
                        for (int m = 0; m < 2; m++) {
                            uint32_t a[4];
                            ldsm4(a, base + off + m * 2048);
                            mma16816(acc[m][ks & 1], a, (ks & 1) ? qf[ks >> 1].z : qf[ks >> 1].x,
                                     (ks & 1) ? qf[ks >> 1].w : qf[ks >> 1].y);
                        }
                    }
                    float a0 = acc[0][0][0] + acc[0][1][0], a1 = acc[0][0][1] + acc[0][1][1];
                    float a2 = acc[0][0][2] + acc[0][1][2], a3 = acc[0][0][3] + acc[0][1][3];
                    float b0 = acc[1][0][0] + acc[1][1][0], b1 = acc[1][0][1] + acc[1][1][1];
                    float b2 = acc[1][0][2] + acc[1][1][2], b3 = acc[1][0][3] + acc[1][1][3];
                    float l0 = (t & 1) ? a2 : a0, l1 = (t & 1) ? a3 : a1;
                    float h0 = (t & 1) ? b2 : b0, h1 = (t & 1) ? b3 : b1;
                    e0 = bf16r(mt ? h0 : l0);
                    e1 = bf16r(mt ? h1 : l1);
                    __syncwarp();
                    if (lane == 0) mbar_arrive(emptyb + st * 8);
                }
                mx0 = fmaxf(mx0, e0);
                mx1 = fmaxf(mx1, e1);
                s_s[tile * 32 + mt * 16 + (t & 1) * 8 + g] = make_float2(e0, e1);
            }
#pragma unroll
            for (int o = 16; o > 0; o >>= 1) {
                mx0 = fmaxf(mx0, __shfl_xor_sync(0xffffffffu, mx0, o));
                mx1 = fmaxf(mx1, __shfl_xor_sync(0xffffffffu, mx1, o));
            }
            if (lane == 0) wmax_s[warp] = make_float2(mx0, mx1);
        }
        bar_sync(1, 256);
        if (ntile < NT && tid < 9) mbar_arrive(emptyb + (tid ? ST_V : ST_V - 1) * 8);

        {
            float m0 = wmax_s[0].x, m1 = wmax_s[0].y;
#pragma unroll
            for (int i = 1; i < 8; i++) {
                m0 = fmaxf(m0, wmax_s[i].x);
                m1 = fmaxf(m1, wmax_s[i].y);
            }
            float l0 = 0.f, l1 = 0.f;
#pragma unroll 1
            for (int i = tid; i < NT * 16; i += 256) {
                const float4 sv = *reinterpret_cast<const float4*>(&s_s[i * 2]);
                const float p00 = ex2((sv.x - m0) * SC), p01 = ex2((sv.z - m0) * SC);
                const float p10 = ex2((sv.y - m1) * SC), p11 = ex2((sv.w - m1) * SC);
                const int it = NT + 1 - (i >> 4), j = i & 15;
                p_s[((it * 2 + 0) * 4 + (j & 3)) * 4 + (j >> 2)] = pack_bf16(p00, p01);
                p_s[((it * 2 + 1) * 4 + (j & 3)) * 4 + (j >> 2)] = pack_bf16(p10, p11);
                l0 += p00 + p01;
                l1 += p10 + p11;
            }
#pragma unroll
            for (int o = 16; o > 0; o >>= 1) {
                l0 += __shfl_xor_sync(0xffffffffu, l0, o);
                l1 += __shfl_xor_sync(0xffffffffu, l1, o);
            }
            if (lane == 0) wsum_s[warp] = make_float2(l0, l1);
            bar_sync(1, 256);
            if (warp == 7 && lane < 4) {
                float l = 0.f;
#pragma unroll
                for (int i = 0; i < 8; i++) l += (lane & 2) ? wsum_s[i].y : wsum_s[i].x;
                const uint32_t tag4 = reinterpret_cast<volatile uint32_t*>(fac_s)[3];
                post_or(&sc->oml[rk][cl * 4 + lane], tagf((lane & 1) ? l : ((lane & 2) ? m1 : m0), tag4));
            }
        }
        asm volatile("barrier.cluster.wait.aligned;" ::: "memory");
    }
}

typedef CUresult (*EncodeFn)(CUtensorMap*, CUtensorMapDataType, cuuint32_t, void*, const cuuint64_t*,
                             const cuuint64_t*, const cuuint32_t*, const cuuint32_t*, CUtensorMapInterleave,
                             CUtensorMapSwizzle, CUtensorMapL2promotion, CUtensorMapFloatOOBfill);

void make_3d(EncodeFn enc, CUtensorMap* m, const void* base, uint64_t d0, uint64_t d1, uint64_t d2, uint64_t s1,
             uint64_t s2, uint32_t b0, uint32_t b1, uint32_t b2, CUtensorMapSwizzle sw, int promo) {
    cuuint64_t gd[3] = {d0, d1, d2};
    cuuint64_t gs[2] = {s1, s2};
    cuuint32_t bx[3] = {b0, b1, b2};
    cuuint32_t es[3] = {1, 1, 1};
    enc(m, CU_TENSOR_MAP_DATA_TYPE_BFLOAT16, 3, const_cast<void*>(base), gd, gs, bx, es,
        CU_TENSOR_MAP_INTERLEAVE_NONE, sw, (CUtensorMapL2promotion)promo, CU_TENSOR_MAP_FLOAT_OOB_FILL_NONE);
}

bool launch(void* const* d_in, void* d_out) {
    static EncodeFn enc = nullptr;
    static Scratch* sc = nullptr;
    if (!enc) {
        cudaDriverEntryPointQueryResult qr;
        void* fn = nullptr;
        cudaGetDriverEntryPoint("cuTensorMapEncodeTiled", &fn, cudaEnableDefault, &qr);
        enc = (EncodeFn)fn;
        cudaGetSymbolAddress((void**)&sc, g_scratch);
        cudaFuncSetAttribute(fused_decode_kernel, cudaFuncAttributeMaxDynamicSharedMemorySize, SMEM_BYTES);
        cudaFuncSetAttribute(fused_decode_kernel, cudaFuncAttributeNonPortableClusterSizeAllowed, 1);
    }
    Maps maps;
    make_3d(enc, &maps.m[0], d_in[1], 64, 16 * SK, 4, 512, 128, 64, 32, 4, CU_TENSOR_MAP_SWIZZLE_128B, 3);
    make_3d(enc, &maps.m[1], d_in[2], 64, 16 * SK, 4, 512, 128, 64, 32, 4, CU_TENSOR_MAP_SWIZZLE_128B, 3);
    make_3d(enc, &maps.m[2], d_in[6], 64, 448, 28, 3584, 128, 64, 32, 4, CU_TENSOR_MAP_SWIZZLE_128B, 3);
    make_3d(enc, &maps.m[3], d_in[7], 64, 448, 28, 3584, 128, 64, 32, 4, CU_TENSOR_MAP_SWIZZLE_128B, 3);
    make_3d(enc, &maps.m[4], d_in[4], 64, 4096, 7, 896, 128, 64, 128, 1, CU_TENSOR_MAP_SWIZZLE_128B, 2);
    make_3d(enc, &maps.m[5], d_in[8], 64, 1792, 7, 896, 128, 64, 112, 1, CU_TENSOR_MAP_SWIZZLE_128B, 2);
    cudaLaunchConfig_t cfg = {};
    cfg.gridDim = dim3(NCTA);
    cfg.blockDim = dim3(NTHREADS);
    cfg.dynamicSmemBytes = SMEM_BYTES;
    cfg.stream = cudaStreamPerThread;
    cudaLaunchAttribute at[1];
    at[0].id = cudaLaunchAttributeClusterDimension;
    at[0].val.clusterDim.x = CL;
    at[0].val.clusterDim.y = 1;
    at[0].val.clusterDim.z = 1;
    cfg.attrs = at;
    cfg.numAttrs = 1;
    static int fits = -1;
    if (fits < 0) {
        int n = 0;
        fits = cudaOccupancyMaxActiveClusters(&n, fused_decode_kernel, &cfg) == cudaSuccess && n >= NCL;
        cudaGetLastError();
    }
    if (!fits) return false;
    cudaLaunchKernelEx(&cfg, fused_decode_kernel, (const __nv_bfloat16*)d_in[0], (__nv_bfloat16*)d_out, sc,
                       (const uint4*)d_in[3], maps, g_tune);
    return true;
}

}

namespace plain {

constexpr int D_MODEL = 448;
constexpr int SK = 32768;
constexpr int WIN = 4096;
constexpr int NCTA = 128;
constexpr int NFFN = 112;
constexpr int STAGE = 16384;
constexpr int NS = 13;
constexpr int ST_WQ = 0;
constexpr int ST_K = 2;
constexpr int ST_V = 18;
constexpr int ST_G = 34;
constexpr int ST_WO = 36;
constexpr int ST_WD = 38;
constexpr int NST = 39;
constexpr int NEMPTY = NST - NS;
constexpr int BAR_STAT = NST + NEMPTY;
constexpr int BAR_H = BAR_STAT + 1;
constexpr int BAR_O = BAR_STAT + 2;
constexpr int NBAR = BAR_STAT + 3;
constexpr int NTHREADS = 384;
constexpr int N0 = 4;
constexpr int SMEM_BYTES = NS * STAGE + 1024;
constexpr unsigned SPIN_LIMIT = 1u << 24;

__device__ unsigned int g_epoch[NCTA];
__device__ __align__(128) unsigned int g_qbuf[2][4096];
__device__ __align__(128) float g_oval[8][16][16][32];
__device__ __align__(128) float g_oml[16][32];
__device__ __align__(128) float g_fbuf[NFFN][NCTA][8];

__device__ __forceinline__ uint32_t globaltimer_lo() {
    uint32_t t;
    asm volatile("mov.u32 %0, %globaltimer_lo;" : "=r"(t));
    return t;
}
__device__ __forceinline__ uint32_t smem_u32(const void* p) {
    return (uint32_t)__cvta_generic_to_shared(p);
}
__device__ __forceinline__ void mbar_init(uint32_t bar, uint32_t cnt) {
    asm volatile("mbarrier.init.shared::cta.b64 [%0], %1;" ::"r"(bar), "r"(cnt) : "memory");
}
__device__ __forceinline__ void mbar_expect_tx(uint32_t bar, uint32_t bytes) {
    asm volatile("mbarrier.arrive.expect_tx.shared::cta.b64 _, [%0], %1;" ::"r"(bar), "r"(bytes) : "memory");
}
__device__ __forceinline__ void mbar_arrive(uint32_t bar) {
    asm volatile("mbarrier.arrive.shared::cta.b64 _, [%0];" ::"r"(bar) : "memory");
}
__device__ __forceinline__ void mbar_wait(uint32_t bar) {
    unsigned n = 0;
    uint32_t ok;
    do {
        asm volatile(
            "{\n.reg .pred p;\n"
            "mbarrier.try_wait.parity.shared::cta.b64 p, [%1], 0;\n"
            "selp.u32 %0, 1, 0, p;\n}"
            : "=r"(ok) : "r"(bar) : "memory");
        if (++n > SPIN_LIMIT) __trap();
    } while (!ok);
}
__device__ __forceinline__ void mbar_nap(uint32_t bar, uint32_t ns) {
    asm volatile(
        "{\n.reg .pred p;\n"
        "mbarrier.try_wait.parity.shared::cta.b64 p, [%0], 0, %1;\n}"
        ::"r"(bar), "r"(ns) : "memory");
}
__device__ __forceinline__ uint32_t mbar_test(uint32_t bar) {
    uint32_t ok;
    asm volatile(
        "{\n.reg .pred p;\n"
        "mbarrier.test_wait.parity.shared::cta.b64 p, [%1], 0;\n"
        "selp.u32 %0, 1, 0, p;\n}"
        : "=r"(ok) : "r"(bar) : "memory");
    return ok;
}
__device__ __forceinline__ void tma_3d(uint32_t dst, const void* m, int c0, int c1, int c2, uint32_t bar) {
    asm volatile(
        "cp.async.bulk.tensor.3d.shared::cluster.global.mbarrier::complete_tx::bytes [%0], [%1, {%3, %4, %5}], [%2];"
        ::"r"(dst), "l"(m), "r"(bar), "r"(c0), "r"(c1), "r"(c2) : "memory");
}
__device__ __forceinline__ void prefetch_map(const CUtensorMap* m) {
    asm volatile("prefetch.tensormap [%0];" ::"l"(m) : "memory");
}
__device__ __forceinline__ void ldsm4(uint32_t (&a)[4], uint32_t addr) {
    asm volatile("ldmatrix.sync.aligned.m8n8.x4.shared.b16 {%0,%1,%2,%3}, [%4];"
                 : "=r"(a[0]), "=r"(a[1]), "=r"(a[2]), "=r"(a[3]) : "r"(addr) : "memory");
}
__device__ __forceinline__ void ldsm4t(uint32_t (&a)[4], uint32_t addr) {
    asm volatile("ldmatrix.sync.aligned.m8n8.x4.trans.shared.b16 {%0,%1,%2,%3}, [%4];"
                 : "=r"(a[0]), "=r"(a[1]), "=r"(a[2]), "=r"(a[3]) : "r"(addr) : "memory");
}
__device__ __forceinline__ void mma16816(float (&c)[4], const uint32_t (&a)[4], uint32_t b0, uint32_t b1) {
    asm volatile(
        "mma.sync.aligned.m16n8k16.row.col.f32.bf16.bf16.f32 {%0,%1,%2,%3}, {%4,%5,%6,%7}, {%8,%9}, {%0,%1,%2,%3};"
        : "+f"(c[0]), "+f"(c[1]), "+f"(c[2]), "+f"(c[3])
        : "r"(a[0]), "r"(a[1]), "r"(a[2]), "r"(a[3]), "r"(b0), "r"(b1));
}
__device__ __forceinline__ void bar_sync(int id, int n) {
    asm volatile("bar.sync %0, %1;" ::"r"(id), "r"(n) : "memory");
}
__device__ __forceinline__ void bar_arrive(int id, int n) {
    asm volatile("bar.arrive %0, %1;" ::"r"(id), "r"(n) : "memory");
}
__device__ __forceinline__ float bf16r(float x) { return __bfloat162float(__float2bfloat16_rn(x)); }
__device__ __forceinline__ uint32_t pack_bf16(float lo, float hi) {
    __nv_bfloat162 v = __floats2bfloat162_rn(lo, hi);
    return *reinterpret_cast<uint32_t*>(&v);
}
__device__ __forceinline__ float ex2(float x) {
    float y;
    asm("ex2.approx.ftz.f32 %0, %1;" : "=f"(y) : "f"(x));
    return y;
}
__device__ __forceinline__ void st_relaxed(void* p, uint32_t v) {
    asm volatile("st.relaxed.gpu.global.u32 [%0], %1;" ::"l"(p), "r"(v) : "memory");
}
__device__ __forceinline__ uint32_t ld_relaxed(const void* p) {
    uint32_t v;
    asm volatile("ld.relaxed.gpu.global.u32 %0, [%1];" : "=r"(v) : "l"(p) : "memory");
    return v;
}
__device__ __forceinline__ uint2 ld_relaxed2(const void* p) {
    uint2 v;
    asm volatile("ld.relaxed.gpu.global.v2.u32 {%0,%1}, [%2];" : "=r"(v.x), "=r"(v.y) : "l"(p) : "memory");
    return v;
}
__device__ __forceinline__ uint4 ld_relaxed4(const void* p) {
    uint4 v;
    asm volatile("ld.relaxed.gpu.global.v4.u32 {%0,%1,%2,%3}, [%4];"
                 : "=r"(v.x), "=r"(v.y), "=r"(v.z), "=r"(v.w) : "l"(p) : "memory");
    return v;
}
__device__ __forceinline__ void ld_relaxed2_if(uint2& v, const void* p, uint32_t pred) {
    asm volatile("{\n.reg .pred p;\nsetp.ne.u32 p, %3, 0;\n@p ld.relaxed.gpu.global.v2.u32 {%0,%1}, [%2];\n}"
                 : "+r"(v.x), "+r"(v.y) : "l"(p), "r"(pred) : "memory");
}
__device__ __forceinline__ void ld_relaxed4_if(uint4& v, const void* p, uint32_t pred) {
    asm volatile("{\n.reg .pred p;\nsetp.ne.u32 p, %5, 0;\n@p ld.relaxed.gpu.global.v4.u32 {%0,%1,%2,%3}, [%4];\n}"
                 : "+r"(v.x), "+r"(v.y), "+r"(v.z), "+r"(v.w) : "l"(p), "r"(pred) : "memory");
}
__device__ __forceinline__ uint32_t tagf(float v, uint32_t tag4) { return (__float_as_uint(v) & ~15u) | tag4; }
__device__ __forceinline__ float sel4(const float (&c)[4], int t) {
    float lo = (t & 1) ? c[1] : c[0];
    float hi = (t & 1) ? c[3] : c[2];
    return (t & 2) ? hi : lo;
}

struct Maps {
    CUtensorMap m[7];
};

__global__ void __launch_bounds__(NTHREADS, 1)
fused_decode_kernel(const __grid_constant__ Maps maps, const __nv_bfloat16* __restrict__ x,
                    __nv_bfloat16* __restrict__ out, const unsigned char* __restrict__ wq_raw,
                    const unsigned char* __restrict__ k_raw, const unsigned char* __restrict__ wg_raw,
                    const unsigned char* __restrict__ wu_raw) {
    extern __shared__ unsigned char smem_raw[];
    __shared__ __align__(8) uint64_t bars[NBAR];
    __shared__ __align__(16) int4 sched_s[NST];
    __shared__ __align__(16) float2 s_s[512];
    __shared__ __align__(16) uint32_t p_s[512];
    __shared__ __align__(16) uint32_t xn_s[2 * 228];
    __shared__ __align__(16) uint32_t q_s[2 * 132];
    __shared__ __align__(16) uint32_t oh_s[2][28];
    __shared__ __align__(16) float2 wmax_s[8];
    __shared__ __align__(16) float2 wsum_s[8];
    __shared__ __align__(8) float fac_s[2];

    const int tid = threadIdx.x;
    const int warp = tid >> 5;
    const int lane = tid & 31;
    const int cta = blockIdx.x;
    const int bh = cta >> 3;
    const int sp = cta & 7;
    const int b = bh >> 3;
    const int hkv = bh & 7;
    const bool has_ffn = cta < NFFN;
    const uint32_t ring = (smem_u32(smem_raw) + 1023u) & ~1023u;
    const uint32_t fullb = smem_u32(bars);
    const uint32_t emptyb = fullb + NST * 8;
    const int kvrow = bh * SK + (SK - WIN) + sp * 32;
#define TROW(j) (kvrow + (j) * 256)

    uint4 w[8] = {};
    if (warp == 11) {
        if ((0 & 1) && has_ffn) {
            const float* fb = &g_fbuf[cta][lane >> 1][(lane & 1) * 4];
#pragma unroll
            for (int r = 0; r < 8; r++) w[r] = ld_relaxed4(fb + r * 128);
        }
    } else if (warp == 10) {
        if (0 & 2) {
            const float* ib = &g_oval[hkv][b * 8 + sp][(lane >> 4) * 8][(lane & 15) * 2];
#pragma unroll
            for (int s = 0; s < 8; s++) { const uint2 v = ld_relaxed2(ib + s * 32); w[s].x = v.x; w[s].y = v.y; }
        }
    } else if (warp >= 4 && warp < 8) {
        if (0 & 4) w[0] = ld_relaxed4(&g_qbuf[b][hkv * 512 + (tid - 128) * 4]);
    }
    uint32_t xr[7];
    uint32_t t0 = 0;
    if (warp == 8) {
        if (lane == 0) {
#pragma unroll
            for (int i = 0; i < N0; i++) mbar_init(fullb + i * 8, 1);
            asm volatile("fence.proxy.async.shared::cta;" ::: "memory");
#pragma unroll
            for (int i = 0; i < N0; i++) {
                mbar_expect_tx(fullb + i * 8, i < ST_K ? 14336 : STAGE);
                if (i < ST_K) tma_3d(ring + i * STAGE, &maps.m[0], cta * 32, 0, i, fullb + i * 8);
                else tma_3d(ring + i * STAGE, &maps.m[1], 0, TROW(i - ST_K), 0, fullb + i * 8);
            }
            t0 = globaltimer_lo();
#pragma unroll
            for (int i = 2; i < 7; i++) prefetch_map(&maps.m[i]);
        }
    } else if (warp < 2) {
        const uint32_t* xp = reinterpret_cast<const uint32_t*>(x) + warp * 224;
#pragma unroll
        for (int i = 0; i < 7; i++) xr[i] = __ldg(xp + lane + 32 * i);
    } else if (warp == 9) {
        t0 = globaltimer_lo() + 250;
        for (int i = lane; i < NST; i += 32) {
            int map, bytes = STAGE, c0 = 0, c1, c2 = 0;
            if (i < ST_K + 16) {
                map = 1; c1 = TROW(i - ST_K);
            } else if (i >= ST_V && i < ST_V + 16) {
                map = 2; c1 = TROW(i - ST_V);
            } else if (i < ST_WO) {
                map = 3 + i - ST_G; c0 = cta * 16; c1 = 0; bytes = has_ffn ? 14336 : 0;
            } else if (i < ST_WD) {
                map = 5; c1 = hkv * 512 + (b * 8 + sp) * 32; c2 = (i - ST_WO) * 4;
            } else {
                map = 6; c1 = cta * 16; bytes = has_ffn ? 14336 : 0;
            }
            const int dep = i - (i < ST_V + 16 ? 8 : 8);
            float u = (float)i - 0.25f - 0.235f * (float)(i > ST_G + 1 ? 2 : i > ST_G ? 1 : 0) -
                            (i == ST_WD ? 0.25f : 0.f) - 1.0f;
            const int tm = u > 0.f ? (int)(u * (float)645) : 0;
            sched_s[i] = make_int4((map * 128) | (bytes << 16), c0, c1, c2 | ((dep < 0 ? 0 : dep) << 8) | (tm << 16));
        }
    } else if (lane == 0 && warp < 8) {
#pragma unroll 1
        for (int i = N0 + warp - 2; i < NBAR; i += 6) {
            const int e = i - NST;
            mbar_init(fullb + i * 8, (e >= ST_V && e < NEMPTY) ? 8 : (e >= 0 && e < ST_K) ? 2 : 1);
        }
        asm volatile("fence.proxy.async.shared::cta;" ::: "memory");
    }
    const uint32_t epoch = ld_relaxed(&g_epoch[cta]);
    __syncthreads();

    if (warp == 8) {
        if (lane == 0) {
            int slot = N0;
#pragma unroll 1
            for (int i = N0; i < NST; i++) {
                const int4 e = sched_s[i];
                if (i >= 8) mbar_wait(fullb + ((e.w >> 8) & 0xff) * 8);
                if (i >= NS) mbar_wait(emptyb + (i - NS) * 8);
                if (645 > 0) {
                    const uint32_t tm = (uint32_t)e.w >> 16;
                    unsigned n = 0;
                    while (globaltimer_lo() - t0 < tm && ++n < 4096u) {}
                }
                const uint32_t bytes = (uint32_t)e.x >> 16;
                mbar_expect_tx(fullb + i * 8, bytes);
                if (bytes)
                    tma_3d(ring + slot * STAGE, reinterpret_cast<const unsigned char*>(&maps) + (e.x & 0xffff), e.y,
                           e.z, e.w & 0xff, fullb + i * 8);
                if (++slot == NS) slot = 0;
            }
            g_epoch[cta] = epoch + 1;
        }
        return;
    }

    const uint32_t tag16 = (epoch % 65535u) + 1u;
    const uint32_t tag4 = (epoch % 15u) + 1u;
    const int g = lane >> 2;
    const int t = lane & 3;
    const int lrow = (lane & 7) + ((lane >> 4) << 3);
    const int lcol = (lane >> 3) & 1;
    const float SC = 0.0625f * 1.4426950408889634f;

    if (warp == 9) {
        bar_sync(4, 96);
        if (has_ffn) {
            uint32_t xf[28][2];
#pragma unroll
            for (int ks = 0; ks < 28; ks++) {
                xf[ks][0] = xn_s[ks * 8 + (g & 1) * 228 + t];
                xf[ks][1] = xn_s[ks * 8 + (g & 1) * 228 + t + 4];
            }
            float hv = 1.f;
#pragma unroll 1
            for (int j = 0; j < 2; j++) {
                const uint32_t base = ring + ((ST_G + j) % NS) * STAGE + lrow * 32 + ((lcol ^ ((lrow >> 2) & 1)) << 4);
                float acc[4][4] = {};
                mbar_wait(fullb + (ST_G + j) * 8);
#pragma unroll
                for (int ks = 0; ks < 28; ks++) {
                    uint32_t a[4];
                    ldsm4t(a, base + ks * 512);
                    mma16816(acc[ks & 3], a, xf[ks][0], xf[ks][1]);
                }
                float c[4];
#pragma unroll
                for (int i = 0; i < 4; i++) c[i] = (acc[0][i] + acc[1][i]) + (acc[2][i] + acc[3][i]);
                hv *= bf16r(sel4(c, t));
                if (ST_G < NEMPTY) {
                    __syncwarp();
                    if (lane == 0) mbar_arrive(emptyb + (ST_G + j) * 8);
                }
            }
            reinterpret_cast<__nv_bfloat16*>(&oh_s[t & 1][16])[g + (t >> 1) * 8] = __float2bfloat16_rn(hv);
            __syncwarp();
            if (lane == 0) mbar_arrive(fullb + BAR_H * 8);
        } else if (ST_G < NEMPTY && lane < 2) {
            mbar_arrive(emptyb + (ST_G + lane) * 8);
        }
        return;
    }

    if (warp == 10) {
        const float* ib = &g_oval[hkv][b * 8 + sp][(lane >> 4) * 8][(lane & 15) * 2];
        mbar_wait(fullb + (27) * 8);
        uint2 v[8];
        unsigned n = 0;
        uint32_t pend = 0;
#pragma unroll
        for (int s = 0; s < 8; s++) {
            v[s] = make_uint2(w[s].x, w[s].y);
            if (((v[s].x ^ tag4) | (v[s].y ^ tag4)) & 15u) pend |= 1u << s;
        }
        while (true) {
#pragma unroll
            for (int s = 0; s < 8; s++) ld_relaxed2_if(v[s], ib + s * 32, pend & (1u << s));
            pend = 0;
#pragma unroll
            for (int s = 0; s < 8; s++)
                if (((v[s].x ^ tag4) | (v[s].y ^ tag4)) & 15u) pend |= 1u << s;
            if (!__any_sync(0xffffffffu, pend)) break;
            if (++n > SPIN_LIMIT) __trap();
            mbar_nap(fullb + (ST_V + 12) * 8, 4000);
        }
        float o0 = 0.f, o1 = 0.f;
#pragma unroll
        for (int s = 0; s < 8; s++) {
            o0 += __uint_as_float(v[s].x);
            o1 += __uint_as_float(v[s].y);
        }
        oh_s[lane >> 4][lane & 15] = pack_bf16(o0, o1);
        __syncwarp();
        if (lane == 0) mbar_arrive(fullb + BAR_O * 8);
        return;
    }
    if (warp == 11) {
        {
            uint32_t sw;
            unsigned n = 0;
            while (true) {
                sw = ld_relaxed(&g_oml[bh][lane]);
                if (__all_sync(0xffffffffu, (sw & 15u) == tag4)) break;
                if (++n > SPIN_LIMIT) __trap();
                __nanosleep(500);
            }
            const float val = __uint_as_float(sw & ~15u);
            const float ms = __shfl_sync(0xffffffffu, val, lane & ~1);
            float mm = ms;
#pragma unroll
            for (int o = 4; o < 32; o <<= 1) mm = fmaxf(mm, __shfl_xor_sync(0xffffffffu, mm, o));
            float den = val * ex2((ms - mm) * SC);
#pragma unroll
            for (int o = 4; o < 32; o <<= 1) den += __shfl_xor_sync(0xffffffffu, den, o);
            if ((lane >> 2) == sp && (lane & 1)) fac_s[(lane >> 1) & 1] = __fdividef(ex2((ms - mm) * SC), den);
            __syncwarp();
            if (lane == 0) mbar_arrive(fullb + BAR_STAT * 8);
        }
        if (!has_ffn) return;
        const int oidx = (lane & 1) * D_MODEL + cta * 4 + ((lane >> 1) & 3);
        const float xres = __bfloat162float(x[oidx]);
        const float* fb = &g_fbuf[cta][lane >> 1][(lane & 1) * 4];
        mbar_wait(fullb + (27) * 8);
        unsigned n = 0;
        uint32_t pend = 0;
#pragma unroll
        for (int r = 0; r < 8; r++)
            if (((w[r].x ^ tag4) | (w[r].y ^ tag4) | (w[r].z ^ tag4) | (w[r].w ^ tag4)) & 15u) pend |= 1u << r;
        while (true) {
#pragma unroll
            for (int r = 0; r < 8; r++) ld_relaxed4_if(w[r], fb + r * 128, pend & (1u << r));
            pend = 0;
#pragma unroll
            for (int r = 0; r < 8; r++)
                if (((w[r].x ^ tag4) | (w[r].y ^ tag4) | (w[r].z ^ tag4) | (w[r].w ^ tag4)) & 15u) pend |= 1u << r;
            if (!__any_sync(0xffffffffu, pend)) break;
            if (++n > SPIN_LIMIT) __trap();
            mbar_nap(fullb + BAR_O * 8, 4000);
        }
        float a[4] = {};
#pragma unroll
        for (int r = 0; r < 8; r++) {
            a[0] += __uint_as_float(w[r].x);
            a[1] += __uint_as_float(w[r].y);
            a[2] += __uint_as_float(w[r].z);
            a[3] += __uint_as_float(w[r].w);
        }
#pragma unroll
        for (int o = 2; o < 32; o <<= 1)
#pragma unroll
            for (int i = 0; i < 4; i++) a[i] += __shfl_xor_sync(0xffffffffu, a[i], o);
        const float mine = sel4(a, lane & 3);
        const float other = __shfl_sync(0xffffffffu, sel4(a, (lane ^ 1) & 3), lane ^ 1);
        const float tot = (((lane >> 2) & 1) == (lane & 1)) ? mine : other;
        if (lane < 8) out[oidx] = __float2bfloat16_rn(xres + tot);
        return;
    }

    if (warp < 2) {
        float v[14];
        float s = 0.f;
#pragma unroll
        for (int i = 0; i < 7; i++) {
            v[2 * i] = __uint_as_float(xr[i] << 16);
            v[2 * i + 1] = __uint_as_float(xr[i] & 0xffff0000u);
            s += v[2 * i] + v[2 * i + 1];
        }
#pragma unroll
        for (int o = 16; o > 0; o >>= 1) s += __shfl_xor_sync(0xffffffffu, s, o);
        const float mean = s * (1.0f / D_MODEL);
        float ss = 0.f;
#pragma unroll
        for (int i = 0; i < 14; i++) ss += (v[i] - mean) * (v[i] - mean);
#pragma unroll
        for (int o = 16; o > 0; o >>= 1) ss += __shfl_xor_sync(0xffffffffu, ss, o);
        const float mb = bf16r(mean);
        const float var = bf16r(ss * (1.0f / D_MODEL));
        const float rsd = __frcp_rn(bf16r(__fsqrt_rn(bf16r(var + 1e-5f))));
#pragma unroll
        for (int i = 0; i < 7; i++)
            xn_s[warp * 228 + lane + 32 * i] =
                pack_bf16(bf16r(v[2 * i] - mb) * rsd, bf16r(v[2 * i + 1] - mb) * rsd);
        bar_arrive(4, 96);
        bar_sync(3, 64);

        float acc[2][4] = {};
#pragma unroll 1
        for (int hf = 0; hf < 2; hf++) {
            mbar_wait(fullb + (ST_WQ + hf) * 8);
            const uint32_t base = ring + (ST_WQ + hf) * STAGE;
#pragma unroll
            for (int ks = 0; ks < 14; ks++) {
                const int row = ks * 16 + lrow;
                uint32_t a[4];
                ldsm4t(a, base + row * 64 + (((warp * 2 + lcol) ^ ((row >> 1) & 3)) << 4));
                const int kk = (hf * 14 + ks) * 8 + (g & 1) * 228 + t;
                mma16816(acc[ks & 1], a, xn_s[kk], xn_s[kk + 4]);
            }
            __syncwarp();
            if (lane == 0) mbar_arrive(emptyb + (ST_WQ + hf) * 8);
        }
        float c[4];
#pragma unroll
        for (int i = 0; i < 4; i++) c[i] = acc[0][i] + acc[1][i];
        const float qv = sel4(c, t);
        const int col = cta * 32 + warp * 16 + g + (t >> 1) * 8;
        st_relaxed(&g_qbuf[t & 1][col], (uint32_t)__bfloat16_as_ushort(__float2bfloat16_rn(qv)) | (tag16 << 16));
    } else if (warp >= 4) {
        const int j = tid - 128;
        const unsigned int* qp = &g_qbuf[b][hkv * 512 + j * 4];
        mbar_wait(fullb + 5 * 8);
        uint4 qw = w[0];
        unsigned n = 0;
        while ((((qw.x >> 16) ^ tag16) | ((qw.y >> 16) ^ tag16) | ((qw.z >> 16) ^ tag16) | ((qw.w >> 16) ^ tag16)) != 0) {
            qw = ld_relaxed4(qp);
            if (++n > SPIN_LIMIT) __trap();
        }
        *reinterpret_cast<uint2*>(&q_s[(j >> 6) * 132 + (j & 63) * 2]) =
            make_uint2((qw.x & 0xffffu) | (qw.y << 16), (qw.z & 0xffffu) | (qw.w << 16));
    }
    bar_sync(1, 256);

    {
        uint32_t qf[16][2];
#pragma unroll
        for (int ks = 0; ks < 16; ks++) {
            qf[ks][0] = q_s[(g & 1) * 132 + ks * 8 + t];
            qf[ks][1] = q_s[(g & 1) * 132 + ks * 8 + 4 + t];
        }
        float mx0 = -INFINITY, mx1 = -INFINITY;
        const uint32_t koff = ((lane & 7) + ((lane >> 3) & 1) * 8) * 128;
#pragma unroll 1
        for (int it = 0; it < 2; it++) {
            const int tile = warp + it * 8;
            const int st = ST_K + tile;
            mbar_wait(fullb + st * 8);
            const uint32_t base = ring + (st % NS) * STAGE + koff;
            float acc[2][2][4] = {};
#pragma unroll
            for (int ks = 0; ks < 16; ks++) {
                const uint32_t off = (ks >> 2) * 4096 + ((((ks & 3) * 2 + (lane >> 4)) ^ (lane & 7)) << 4);
#pragma unroll
                for (int mt = 0; mt < 2; mt++) {
                    uint32_t a[4];
                    ldsm4(a, base + off + mt * 2048);
                    mma16816(acc[mt][ks & 1], a, qf[ks][0], qf[ks][1]);
                }
            }
            __syncwarp();
            if (lane == 0) mbar_arrive(emptyb + st * 8);
            const int mt = t >> 1;
            float e0, e1;
            {
                float a0 = acc[0][0][0] + acc[0][1][0], a1 = acc[0][0][1] + acc[0][1][1];
                float a2 = acc[0][0][2] + acc[0][1][2], a3 = acc[0][0][3] + acc[0][1][3];
                float b0 = acc[1][0][0] + acc[1][1][0], b1 = acc[1][0][1] + acc[1][1][1];
                float b2 = acc[1][0][2] + acc[1][1][2], b3 = acc[1][0][3] + acc[1][1][3];
                float l0 = (t & 1) ? a2 : a0, l1 = (t & 1) ? a3 : a1;
                float h0 = (t & 1) ? b2 : b0, h1 = (t & 1) ? b3 : b1;
                e0 = mt ? h0 : l0;
                e1 = mt ? h1 : l1;
            }
            e0 = bf16r(e0);
            e1 = bf16r(e1);
            mx0 = fmaxf(mx0, e0);
            mx1 = fmaxf(mx1, e1);
            s_s[tile * 32 + mt * 16 + (t & 1) * 8 + g] = make_float2(e0, e1);
        }
#pragma unroll
        for (int o = 16; o > 0; o >>= 1) {
            mx0 = fmaxf(mx0, __shfl_xor_sync(0xffffffffu, mx0, o));
            mx1 = fmaxf(mx1, __shfl_xor_sync(0xffffffffu, mx1, o));
        }
        if (lane == 0) wmax_s[warp] = make_float2(mx0, mx1);
    }
    bar_sync(1, 256);

    {
        float m0 = wmax_s[0].x, m1 = wmax_s[0].y;
#pragma unroll
        for (int i = 1; i < 8; i++) {
            m0 = fmaxf(m0, wmax_s[i].x);
            m1 = fmaxf(m1, wmax_s[i].y);
        }
        const float4 sv = *reinterpret_cast<const float4*>(&s_s[tid * 2]);
        const float p00 = ex2((sv.x - m0) * SC), p01 = ex2((sv.z - m0) * SC);
        const float p10 = ex2((sv.y - m1) * SC), p11 = ex2((sv.w - m1) * SC);
        const int T = tid >> 4, j = tid & 15;
        p_s[((T * 2 + 0) * 4 + (j & 3)) * 4 + (j >> 2)] = pack_bf16(p00, p01);
        p_s[((T * 2 + 1) * 4 + (j & 3)) * 4 + (j >> 2)] = pack_bf16(p10, p11);
        float l0 = p00 + p01, l1 = p10 + p11;
#pragma unroll
        for (int o = 16; o > 0; o >>= 1) {
            l0 += __shfl_xor_sync(0xffffffffu, l0, o);
            l1 += __shfl_xor_sync(0xffffffffu, l1, o);
        }
        if (lane == 0) wsum_s[warp] = make_float2(l0, l1);
        bar_sync(1, 256);
        if (warp == 7 && lane < 4) {
            float l = 0.f;
#pragma unroll
            for (int i = 0; i < 8; i++) l += (lane & 2) ? wsum_s[i].y : wsum_s[i].x;
            st_relaxed(&g_oml[bh][sp * 4 + lane], tagf((lane & 1) ? l : ((lane & 2) ? m1 : m0), tag4));
        }
    }

    {
        float oacc[2][4] = {};
        const uint32_t voff = (warp >> 1) * 4096 + lrow * 128;
        const int c16 = (warp & 1) * 4 + lcol;
        float* op = &g_oval[hkv][(t & 1) * 8 + warp][b * 8 + sp][g + (t >> 1) * 8];
        float fac = 0.f;
        int slot = ST_V % NS;
#pragma unroll 1
        for (int tile = 0; tile < 16; tile++) {
            const int st = ST_V + tile;
            const uint4 pf = *reinterpret_cast<const uint4*>(&p_s[((tile * 2 + (g & 1)) * 4 + t) * 4]);
            if (tile == 15) {
                mbar_wait(fullb + BAR_STAT * 8);
                fac = fac_s[t & 1];
            }
            mbar_wait(fullb + st * 8);
            const uint32_t base = ring + slot * STAGE + voff;
            uint32_t a[2][2][4];
#pragma unroll
            for (int kk = 0; kk < 2; kk++)
#pragma unroll
                for (int mt = 0; mt < 2; mt++)
                    ldsm4t(a[kk][mt], base + kk * 2048 + (((c16 + mt * 2) ^ (lane & 7)) << 4));
            mma16816(oacc[0], a[0][0], pf.x, pf.y);
            mma16816(oacc[1], a[0][1], pf.x, pf.y);
            mma16816(oacc[0], a[1][0], pf.z, pf.w);
            mma16816(oacc[1], a[1][1], pf.z, pf.w);
            __syncwarp();
            if (st < NEMPTY && lane == 0) mbar_arrive(emptyb + st * 8);
            if (++slot == NS) slot = 0;
        }
        st_relaxed(op, tagf(sel4(oacc[0], t) * fac, tag4));
        st_relaxed(op + 16, tagf(sel4(oacc[1], t) * fac, tag4));
    }

    if (warp < 7) {
        const int st = ST_WO + (warp >> 2);
        const uint32_t base = ring + (st % NS) * STAGE + (warp & 3) * 4096 + lrow * 128;
        const uint32_t based = ring + (ST_WD % NS) * STAGE + warp * 2048 + lrow * 128;
        float* fp = &g_fbuf[warp * 16 + (g >> 2) + (t >> 1) * 2][cta][(g & 3) * 2 + (t & 1)];
        uint32_t a[2][4][4];
        mbar_wait(fullb + st * 8);
#pragma unroll
        for (int ks = 0; ks < 2; ks++)
#pragma unroll
            for (int mt = 0; mt < 4; mt++)
                ldsm4t(a[ks][mt], base + ks * 2048 + (((mt * 2 + lcol) ^ (lane & 7)) << 4));
        float acc[4][4] = {};
        uint32_t todo = has_ffn ? 3u : 1u;
        unsigned n = 0;
#pragma unroll 1
        while (todo) {
            if ((todo & 1u) && mbar_test(fullb + BAR_O * 8)) {
                const uint32_t b00 = oh_s[g & 1][t], b01 = oh_s[g & 1][4 + t];
                const uint32_t b10 = oh_s[g & 1][8 + t], b11 = oh_s[g & 1][12 + t];
#pragma unroll
                for (int mt = 0; mt < 4; mt++) mma16816(acc[mt], a[0][mt], b00, b01);
#pragma unroll
                for (int mt = 0; mt < 4; mt++) mma16816(acc[mt], a[1][mt], b10, b11);
                todo &= ~1u;
            }
            if ((todo & 2u) && mbar_test(fullb + ST_WD * 8) && mbar_test(fullb + BAR_H * 8)) {
                const uint32_t b0 = oh_s[g & 1][16 + t], b1 = oh_s[g & 1][20 + t];
#pragma unroll
                for (int mt = 0; mt < 4; mt++) {
                    uint32_t d[4];
                    ldsm4t(d, based + (((mt * 2 + lcol) ^ (lane & 7)) << 4));
                    mma16816(acc[mt], d, b0, b1);
                }
                todo &= ~2u;
            }
            if (++n > SPIN_LIMIT) __trap();
        }
#pragma unroll
        for (int mt = 0; mt < 4; mt++) st_relaxed(fp + mt * 4 * NCTA * 8, tagf(sel4(acc[mt], t), tag4));
    }
}

typedef CUresult (*EncodeFn)(CUtensorMap*, CUtensorMapDataType, cuuint32_t, void*, const cuuint64_t*,
                             const cuuint64_t*, const cuuint32_t*, const cuuint32_t*, CUtensorMapInterleave,
                             CUtensorMapSwizzle, CUtensorMapL2promotion, CUtensorMapFloatOOBfill);

void make_3d(EncodeFn enc, CUtensorMap* m, const void* base, uint64_t d0, uint64_t d1, uint64_t d2, uint64_t s1,
             uint64_t s2, uint32_t b0, uint32_t b1, uint32_t b2, CUtensorMapSwizzle sw, int promo) {
    cuuint64_t gd[3] = {d0, d1, d2};
    cuuint64_t gs[2] = {s1, s2};
    cuuint32_t bx[3] = {b0, b1, b2};
    cuuint32_t es[3] = {1, 1, 1};
    enc(m, CU_TENSOR_MAP_DATA_TYPE_BFLOAT16, 3, const_cast<void*>(base), gd, gs, bx, es,
        CU_TENSOR_MAP_INTERLEAVE_NONE, sw, (CUtensorMapL2promotion)promo, CU_TENSOR_MAP_FLOAT_OOB_FILL_NONE);
}

void launch(void* const* d_in, void* d_out) {
    static EncodeFn enc = nullptr;
    if (!enc) {
        cudaDriverEntryPointQueryResult qr;
        void* fn = nullptr;
        cudaGetDriverEntryPoint("cuTensorMapEncodeTiled", &fn, cudaEnableDefault, &qr);
        enc = (EncodeFn)fn;
        cudaFuncSetAttribute(fused_decode_kernel, cudaFuncAttributeMaxDynamicSharedMemorySize, SMEM_BYTES);
    }
    Maps maps;
    make_3d(enc, &maps.m[0], d_in[3], 4096, 224, 2, 8192, 224 * 8192, 32, 224, 1, CU_TENSOR_MAP_SWIZZLE_64B, 3);
    make_3d(enc, &maps.m[1], d_in[1], 64, 16 * SK, 4, 512, 128, 64, 32, 4, CU_TENSOR_MAP_SWIZZLE_128B, 3);
    make_3d(enc, &maps.m[2], d_in[2], 64, 16 * SK, 4, 512, 128, 64, 32, 4, CU_TENSOR_MAP_SWIZZLE_128B, 3);
    make_3d(enc, &maps.m[3], d_in[6], 1792, 224, 2, 3584, 224 * 3584, 16, 224, 2, CU_TENSOR_MAP_SWIZZLE_32B, 3);
    make_3d(enc, &maps.m[4], d_in[7], 1792, 224, 2, 3584, 224 * 3584, 16, 224, 2, CU_TENSOR_MAP_SWIZZLE_32B, 3);
    make_3d(enc, &maps.m[5], d_in[4], 64, 4096, 7, 896, 128, 64, 32, 4, CU_TENSOR_MAP_SWIZZLE_128B, 3);
    make_3d(enc, &maps.m[6], d_in[8], 64, 1792, 7, 896, 128, 64, 16, 7, CU_TENSOR_MAP_SWIZZLE_128B, 3);
    fused_decode_kernel<<<NCTA, NTHREADS, SMEM_BYTES, cudaStreamPerThread>>>(
        maps, (const __nv_bfloat16*)d_in[0], (__nv_bfloat16*)d_out, (const unsigned char*)d_in[3],
        (const unsigned char*)d_in[1], (const unsigned char*)d_in[6], (const unsigned char*)d_in[7]);
}
#undef TROW

}

extern "C" void kernel_launch(void* const* d_in, const int* in_sizes, int n_in, void* d_out, int out_size) {
    (void)in_sizes; (void)n_in; (void)out_size;
    if (!clustered::launch(d_in, d_out)) plain::launch(d_in, d_out);
}
```
